```python
import torch

def _softmax(x, axis=-1):
    return torch.softmax(x, dim=axis)
def _gelu(x):
    return torch.nn.functional.gelu(x, approximate="tanh")
def _silu(x):
    return torch.nn.functional.silu(x)
def _sigmoid(x):
    return torch.sigmoid(x)
def _layernorm(x, axis=-1, eps=1e-5):
    m = x.mean(dim=axis, keepdim=True)
    v = x.var(dim=axis, keepdim=True, unbiased=False)
    return (x - m) / torch.sqrt(v + eps)
def _scatter_add(tgt, idx, src, axis=0):
    return tgt.clone().index_add_(axis, idx, src)
def _segment_sum(src, seg, n):
    out = torch.zeros((n,) + src.shape[1:], dtype=src.dtype)
    return out.index_add_(0, seg, src)
def _pad(x, pw):
    flat = tuple(v for pair in reversed(pw) for v in pair)
    return torch.nn.functional.pad(x, flat)

kernel_name = 'standalone__modern_conv_block_slak__vision'

def setup_inputs():

    _w = (lambda a: (lambda t: t.to(torch.bfloat16) if t.is_floating_point() else t)(torch.as_tensor(a)))
    H = W = 512
    C = 96
    K = 1
    return {
        "x": _w((lambda *s: torch.randn(*s, dtype=torch.bfloat16) * 0.05)(1, H, W, C)),
        "dw": _w((lambda *s: torch.randn(*s, dtype=torch.bfloat16) * 0.05)(K, K, C)),
        "w1": _w((lambda *s: torch.randn(*s, dtype=torch.bfloat16) * 0.05)(C, 4 * C)),
        "w2": _w((lambda *s: torch.randn(*s, dtype=torch.bfloat16) * 0.05)(4 * C, C)),
        "grn_g": _w((lambda *s: torch.randn(*s, dtype=torch.bfloat16) * 0.05)(4 * C)),
        "grn_b": _w((lambda *s: torch.randn(*s, dtype=torch.bfloat16) * 0.05)(4 * C)),
    }

def reference(x, dw, w1, w2, grn_g, grn_b):
    B, H, W, C = x.shape
    K = dw.shape[0]
    pad = K // 2
    xp = _pad(x, ((0,0),(pad,pad),(pad,pad),(0,0)))
    out = torch.zeros_like(x)
    for i in range(K):
        for j in range(K):
            out = out + xp[:, i:i+H, j:j+W, :] * dw[i, j][None, None, None, :]
    h = _layernorm(out, axis=-1)
    h = _gelu(h @ w1)
    gx = torch.sqrt((h * h).sum(axis=(1, 2), keepdims=True) + 1e-6)
    nx = gx / (gx.mean(axis=-1, keepdims=True) + 1e-6)
    h = grn_g[None, None, None, :] * (h * nx) + grn_b[None, None, None, :] + h
    return x + h @ w2
```

```cpp
#include <cuda_runtime.h>
#include <cuda_bf16.h>
#include <stdint.h>

#define C_IN 96
#define C_H 384
#define NROWS (512 * 512)
#define TILE_M 64
#define NTILES (NROWS / TILE_M)
#define MAX_CTAS 256

__device__ float g_partial[MAX_CTAS * C_H];

__device__ __forceinline__ uint32_t smem_u32(const void* p) {
    return (uint32_t)__cvta_generic_to_shared(p);
}
__device__ __forceinline__ uint64_t make_desc(uint32_t addr, uint32_t lbo, uint32_t sbo) {
    uint64_t d = 0;
    d |= (uint64_t)((addr & 0x3FFFF) >> 4);
    d |= (uint64_t)((lbo >> 4) & 0x3FFF) << 16;
    d |= (uint64_t)((sbo >> 4) & 0x3FFF) << 32;
    return d;
}
__device__ __forceinline__ void wg_fence() { asm volatile("wgmma.fence.sync.aligned;\n" ::: "memory"); }
__device__ __forceinline__ void wg_commit() { asm volatile("wgmma.commit_group.sync.aligned;\n" ::: "memory"); }
template <int N>
__device__ __forceinline__ void wg_wait() { asm volatile("wgmma.wait_group.sync.aligned %0;\n" ::"n"(N) : "memory"); }

__device__ __forceinline__ float tanh_approx(float x) {
    float y;
    asm("tanh.approx.f32 %0, %1;" : "=f"(y) : "f"(x));
    return y;
}
__device__ __forceinline__ uint32_t pack_bf16(float lo, float hi) {
    uint32_t r;
    asm("cvt.rn.bf16x2.f32 %0, %1, %2;" : "=r"(r) : "f"(hi), "f"(lo));
    return r;
}
__device__ __forceinline__ float bf_lo(uint32_t v) { return __uint_as_float(v << 16); }
__device__ __forceinline__ float bf_hi(uint32_t v) { return __uint_as_float(v & 0xffff0000u); }

__device__ __forceinline__ void wgmma_n64(float (&d)[32], uint32_t a0, uint32_t a1, uint32_t a2, uint32_t a3,
                                          uint64_t bdesc, int scale_d) {
    asm volatile(
        "{\n"
        ".reg .pred p;\n"
        "setp.ne.b32 p, %37, 0;\n"
        "wgmma.mma_async.sync.aligned.m64n64k16.f32.bf16.bf16 "
        "{%0, %1, %2, %3, %4, %5, %6, %7, %8, %9, %10, %11, %12, %13, %14, %15, "
        " %16, %17, %18, %19, %20, %21, %22, %23, %24, %25, %26, %27, %28, %29, %30, %31}, "
        "{%32, %33, %34, %35}, %36, p, 1, 1, 0;\n"
        "}\n"
        : "+f"(d[0]), "+f"(d[1]), "+f"(d[2]), "+f"(d[3]), "+f"(d[4]), "+f"(d[5]), "+f"(d[6]), "+f"(d[7]),
          "+f"(d[8]), "+f"(d[9]), "+f"(d[10]), "+f"(d[11]), "+f"(d[12]), "+f"(d[13]), "+f"(d[14]), "+f"(d[15]),
          "+f"(d[16]), "+f"(d[17]), "+f"(d[18]), "+f"(d[19]), "+f"(d[20]), "+f"(d[21]), "+f"(d[22]), "+f"(d[23]),
          "+f"(d[24]), "+f"(d[25]), "+f"(d[26]), "+f"(d[27]), "+f"(d[28]), "+f"(d[29]), "+f"(d[30]), "+f"(d[31])
        : "r"(a0), "r"(a1), "r"(a2), "r"(a3), "l"(bdesc), "r"(scale_d));
}

__device__ __forceinline__ void wgmma_n96(float (&d)[48], uint32_t a0, uint32_t a1, uint32_t a2, uint32_t a3,
                                          uint64_t bdesc, int scale_d) {
    asm volatile(
        "{\n"
        ".reg .pred p;\n"
        "setp.ne.b32 p, %53, 0;\n"
        "wgmma.mma_async.sync.aligned.m64n96k16.f32.bf16.bf16 "
        "{%0, %1, %2, %3, %4, %5, %6, %7, %8, %9, %10, %11, %12, %13, %14, %15, "
        " %16, %17, %18, %19, %20, %21, %22, %23, %24, %25, %26, %27, %28, %29, %30, %31, "
        " %32, %33, %34, %35, %36, %37, %38, %39, %40, %41, %42, %43, %44, %45, %46, %47}, "
        "{%48, %49, %50, %51}, %52, p, 1, 1, 0;\n"
        "}\n"
        : "+f"(d[0]), "+f"(d[1]), "+f"(d[2]), "+f"(d[3]), "+f"(d[4]), "+f"(d[5]), "+f"(d[6]), "+f"(d[7]),
          "+f"(d[8]), "+f"(d[9]), "+f"(d[10]), "+f"(d[11]), "+f"(d[12]), "+f"(d[13]), "+f"(d[14]), "+f"(d[15]),
          "+f"(d[16]), "+f"(d[17]), "+f"(d[18]), "+f"(d[19]), "+f"(d[20]), "+f"(d[21]), "+f"(d[22]), "+f"(d[23]),
          "+f"(d[24]), "+f"(d[25]), "+f"(d[26]), "+f"(d[27]), "+f"(d[28]), "+f"(d[29]), "+f"(d[30]), "+f"(d[31]),
          "+f"(d[32]), "+f"(d[33]), "+f"(d[34]), "+f"(d[35]), "+f"(d[36]), "+f"(d[37]), "+f"(d[38]), "+f"(d[39]),
          "+f"(d[40]), "+f"(d[41]), "+f"(d[42]), "+f"(d[43]), "+f"(d[44]), "+f"(d[45]), "+f"(d[46]), "+f"(d[47])
        : "r"(a0), "r"(a1), "r"(a2), "r"(a3), "l"(bdesc), "r"(scale_d));
}

__device__ __forceinline__ int k1_to_channel(int k) {
    int t = k >> 4, r = k & 15;
    int q = (r & 7) >> 1;
    int e = (r & 1) + ((r >> 3) << 1);
    return 32 * (t >> 1) + 8 * q + 4 * (t & 1) + e;
}
__device__ __forceinline__ int n2_to_channel(int n) {
    int j = n >> 3, r = n & 7;
    int q = r >> 1, e = r & 1;
    return 32 * (j >> 2) + 8 * q + 2 * (j & 3) + e;
}

#define W1_LBO 128
#define W1_SBO (12 * 128)
#define W2_LBO 128
#define W2_SBO (48 * 128)

__device__ __forceinline__ void stage_w1(unsigned char* sm, const __nv_bfloat16* __restrict__ w1, int tid, int nthreads) {
    for (int it = tid; it < C_H * 12; it += nthreads) {
        int n = it % C_H;
        int kb = it / C_H;
        uint32_t v[4];
#pragma unroll
        for (int p = 0; p < 4; p++) {
            int c0 = k1_to_channel(kb * 8 + 2 * p);
            int c1 = k1_to_channel(kb * 8 + 2 * p + 1);
            uint32_t lo = __bfloat16_as_ushort(w1[c0 * C_H + n]);
            uint32_t hi = __bfloat16_as_ushort(w1[c1 * C_H + n]);
            v[p] = lo | (hi << 16);
        }
        *reinterpret_cast<uint4*>(sm + (n >> 3) * W1_SBO + kb * W1_LBO + (n & 7) * 16) = make_uint4(v[0], v[1], v[2], v[3]);
    }
}

struct XRows {
    uint4 a[3];
    uint4 b[3];
};

__device__ __forceinline__ void load_x(XRows& xr, const __nv_bfloat16* __restrict__ x, int tile, int warp, int lane) {
    int r0 = tile * TILE_M + warp * 16 + (lane >> 2);
    const uint4* p0 = reinterpret_cast<const uint4*>(x + (size_t)r0 * C_IN + (lane & 3) * 8);
    const uint4* p1 = reinterpret_cast<const uint4*>(x + (size_t)(r0 + 8) * C_IN + (lane & 3) * 8);
#pragma unroll
    for (int i = 0; i < 3; i++) {
        xr.a[i] = __ldg(p0 + i * 4);
        xr.b[i] = __ldg(p1 + i * 4);
    }
}

__device__ __forceinline__ void ln_row(const uint4 (&xv)[3], const float* __restrict__ dwv, uint32_t (&y)[12]) {
    float d[24];
    float s = 0.f;
#pragma unroll
    for (int i = 0; i < 3; i++) {
        uint32_t w[4] = {xv[i].x, xv[i].y, xv[i].z, xv[i].w};
#pragma unroll
        for (int p = 0; p < 4; p++) {
            d[i * 8 + 2 * p] = bf_lo(w[p]) * dwv[i * 8 + 2 * p];
            d[i * 8 + 2 * p + 1] = bf_hi(w[p]) * dwv[i * 8 + 2 * p + 1];
            s += d[i * 8 + 2 * p] + d[i * 8 + 2 * p + 1];
        }
    }
    s += __shfl_xor_sync(0xffffffffu, s, 1);
    s += __shfl_xor_sync(0xffffffffu, s, 2);
    float mean = s * (1.0f / C_IN);
    float v = 0.f;
#pragma unroll
    for (int i = 0; i < 24; i++) {
        d[i] -= mean;
        v = fmaf(d[i], d[i], v);
    }
    v += __shfl_xor_sync(0xffffffffu, v, 1);
    v += __shfl_xor_sync(0xffffffffu, v, 2);
    float rstd = rsqrtf(v * (1.0f / C_IN) + 1e-5f);
#pragma unroll
    for (int i = 0; i < 12; i++) y[i] = pack_bf16(d[2 * i] * rstd, d[2 * i + 1] * rstd);
}

#define GELU_C0 0.7978845608028654f
#define GELU_C1 (0.7978845608028654f * 0.044715f)

__device__ __forceinline__ float gelu2(float u) {
    float t = u * u;
    float p = fmaf(t, GELU_C1, GELU_C0);
    float a = p * u;
    float th = tanh_approx(a);
    return fmaf(u, th, u);
}

__global__ void __launch_bounds__(256, 1)
k_stats(const __nv_bfloat16* __restrict__ x, const __nv_bfloat16* __restrict__ dw, const __nv_bfloat16* __restrict__ w1) {
    extern __shared__ __align__(1024) unsigned char smem[];
    unsigned char* s_w1 = smem;
    float* s_dw = reinterpret_cast<float*>(smem + 73728);
    float* s_red = reinterpret_cast<float*>(smem + 73728 + 512);

    const int tid = threadIdx.x;
    const int wg = tid >> 7;
    const int warp = (tid >> 5) & 3;
    const int lane = tid & 31;
    const int q = lane & 3;

    stage_w1(s_w1, w1, tid, 256);
    if (tid < C_IN) s_dw[tid] = __bfloat162float(dw[tid]);
    for (int i = tid; i < C_H; i += 256) s_red[i] = 0.f;
    asm volatile("fence.proxy.async.shared::cta;\n" ::: "memory");
    __syncthreads();

    float dwv[24];
#pragma unroll
    for (int i = 0; i < 3; i++)
#pragma unroll
        for (int p = 0; p < 8; p++) dwv[i * 8 + p] = s_dw[32 * i + 8 * q + p];

    float ss[96];
#pragma unroll
    for (int i = 0; i < 96; i++) ss[i] = 0.f;

    const uint32_t w1_base = smem_u32(s_w1);
    const int nwg = gridDim.x * 2;
    int tile = blockIdx.x * 2 + wg;
    XRows xr;
    if (tile < NTILES) load_x(xr, x, tile, warp, lane);
    for (; tile < NTILES; tile += nwg) {
        uint32_t ya[12], yb[12];
        ln_row(xr.a, dwv, ya);
        ln_row(xr.b, dwv, yb);
        int ntile = tile + nwg;
        if (ntile < NTILES) load_x(xr, x, ntile, warp, lane);

        float S[2][32];
        wg_fence();
#pragma unroll
        for (int t = 0; t < 6; t++) {
            int i = t >> 1, h = t & 1;
            wgmma_n64(S[0], ya[i * 4 + 2 * h], yb[i * 4 + 2 * h], ya[i * 4 + 2 * h + 1], yb[i * 4 + 2 * h + 1],
                      make_desc(w1_base + 2 * t * W1_LBO, W1_LBO, W1_SBO), t != 0);
        }
        wg_commit();
#pragma unroll
        for (int c = 0; c < 6; c++) {
            if (c + 1 < 6) {
                wg_fence();
#pragma unroll
                for (int t = 0; t < 6; t++) {
                    int i = t >> 1, h = t & 1;
                    wgmma_n64(S[(c + 1) & 1], ya[i * 4 + 2 * h], yb[i * 4 + 2 * h], ya[i * 4 + 2 * h + 1],
                              yb[i * 4 + 2 * h + 1],
                              make_desc(w1_base + (c + 1) * 8 * W1_SBO + 2 * t * W1_LBO, W1_LBO, W1_SBO), t != 0);
                }
                wg_commit();
                wg_wait<1>();
            } else {
                wg_wait<0>();
            }
            float(&Sc)[32] = S[c & 1];
#pragma unroll
            for (int j = 0; j < 8; j++) {
                float g0 = gelu2(Sc[4 * j]);
                float g1 = gelu2(Sc[4 * j + 1]);
                float g2 = gelu2(Sc[4 * j + 2]);
                float g3 = gelu2(Sc[4 * j + 3]);
                ss[c * 16 + 2 * j] = fmaf(g0, g0, fmaf(g2, g2, ss[c * 16 + 2 * j]));
                ss[c * 16 + 2 * j + 1] = fmaf(g1, g1, fmaf(g3, g3, ss[c * 16 + 2 * j + 1]));
            }
        }
    }
#pragma unroll
    for (int i = 0; i < 96; i++) {
        float v = ss[i];
        v += __shfl_xor_sync(0xffffffffu, v, 4);
        v += __shfl_xor_sync(0xffffffffu, v, 8);
        v += __shfl_xor_sync(0xffffffffu, v, 16);
        if (lane < 4) {
            int c = i >> 4, j = (i >> 1) & 7, e = i & 1;
            atomicAdd(&s_red[c * 64 + 8 * j + 2 * q + e], v);
        }
    }
    __syncthreads();
    for (int i = tid; i < C_H; i += 256) g_partial[blockIdx.x * C_H + i] = s_red[i] * 0.25f;
}

__global__ void __launch_bounds__(256, 1)
k_main(const __nv_bfloat16* __restrict__ x, const __nv_bfloat16* __restrict__ dw, const __nv_bfloat16* __restrict__ w1,
       const __nv_bfloat16* __restrict__ w2, const __nv_bfloat16* __restrict__ grn_g,
       const __nv_bfloat16* __restrict__ grn_b, __nv_bfloat16* __restrict__ out, int n_part) {
    extern __shared__ __align__(1024) unsigned char smem[];
    unsigned char* s_w1 = smem;
    unsigned char* s_w2 = smem + 73728;
    float* s_dw = reinterpret_cast<float*>(smem + 2 * 73728);
    float* s_c = reinterpret_cast<float*>(smem + 2 * 73728 + 512);
    float* s_s = reinterpret_cast<float*>(smem + 2 * 73728 + 1024);
    float* s_tmp = reinterpret_cast<float*>(smem + 2 * 73728 + 1024 + 1536);

    const int tid = threadIdx.x;
    const int wg = tid >> 7;
    const int warp = (tid >> 5) & 3;
    const int lane = tid & 31;
    const int q = lane & 3;

    stage_w1(s_w1, w1, tid, 256);
    if (tid < C_IN) s_dw[tid] = __bfloat162float(dw[tid]);
    float lsum = 0.f;
    for (int k = tid; k < C_H; k += 256) {
        float a = 0.f;
        for (int b = 0; b < n_part; b++) a += g_partial[b * C_H + k];
        float gx = sqrtf(a + 1e-6f);
        s_s[k] = gx;
        lsum += gx;
    }
#pragma unroll
    for (int o = 16; o > 0; o >>= 1) lsum += __shfl_xor_sync(0xffffffffu, lsum, o);
    if (lane == 0) s_tmp[tid >> 5] = lsum;
    __syncthreads();
    float tot = 0.f;
#pragma unroll
    for (int i = 0; i < 8; i++) tot += s_tmp[i];
    float inv = 1.0f / (tot * (1.0f / C_H) + 1e-6f);
    __syncthreads();
    for (int k = tid; k < C_H; k += 256) {
        float nx = s_s[k] * inv;
        s_s[k] = 0.5f * (1.0f + __bfloat162float(grn_g[k]) * nx);
    }
    if (tid < C_IN) {
        float a = 0.f;
        for (int k = 0; k < C_H; k++) a = fmaf(__bfloat162float(grn_b[k]), __bfloat162float(w2[k * C_IN + tid]), a);
        s_c[tid] = a;
    }
    __syncthreads();
    for (int it = tid; it < C_IN * 48; it += 256) {
        int n = it % C_IN;
        int kb = it / C_IN;
        int ch = n2_to_channel(n);
        uint32_t v[4];
#pragma unroll
        for (int p = 0; p < 4; p++) {
            int k0 = kb * 8 + 2 * p;
            v[p] = pack_bf16(s_s[k0] * __bfloat162float(w2[k0 * C_IN + ch]),
                             s_s[k0 + 1] * __bfloat162float(w2[(k0 + 1) * C_IN + ch]));
        }
        *reinterpret_cast<uint4*>(s_w2 + (n >> 3) * W2_SBO + kb * W2_LBO + (n & 7) * 16) = make_uint4(v[0], v[1], v[2], v[3]);
    }
    asm volatile("fence.proxy.async.shared::cta;\n" ::: "memory");
    __syncthreads();

    float dwv[24];
#pragma unroll
    for (int i = 0; i < 3; i++)
#pragma unroll
        for (int p = 0; p < 8; p++) dwv[i * 8 + p] = s_dw[32 * i + 8 * q + p];

    const uint32_t w1_base = smem_u32(s_w1);
    const uint32_t w2_base = smem_u32(s_w2);
    const int nwg = gridDim.x * 2;
    int tile = blockIdx.x * 2 + wg;
    XRows xr, xn;
    if (tile < NTILES) load_x(xn, x, tile, warp, lane);
    for (; tile < NTILES; tile += nwg) {
        xr = xn;
        uint32_t ya[12], yb[12];
        ln_row(xr.a, dwv, ya);
        ln_row(xr.b, dwv, yb);
        int ntile = tile + nwg;
        if (ntile < NTILES) load_x(xn, x, ntile, warp, lane);

        float O[48];
#pragma unroll
        for (int j = 0; j < 12; j++) {
            float c0 = s_c[32 * (j >> 2) + 8 * q + 2 * (j & 3)];
            float c1 = s_c[32 * (j >> 2) + 8 * q + 2 * (j & 3) + 1];
            O[4 * j] = c0; O[4 * j + 1] = c1; O[4 * j + 2] = c0; O[4 * j + 3] = c1;
        }
        float S[2][32];
        uint32_t hf[16];
        wg_fence();
#pragma unroll
        for (int t = 0; t < 6; t++) {
            int i = t >> 1, h = t & 1;
            wgmma_n64(S[0], ya[i * 4 + 2 * h], yb[i * 4 + 2 * h], ya[i * 4 + 2 * h + 1], yb[i * 4 + 2 * h + 1],
                      make_desc(w1_base + 2 * t * W1_LBO, W1_LBO, W1_SBO), t != 0);
        }
        wg_commit();
#pragma unroll
        for (int c = 0; c < 6; c++) {
            if (c + 1 < 6) {
                wg_fence();
#pragma unroll
                for (int t = 0; t < 6; t++) {
                    int i = t >> 1, h = t & 1;
                    wgmma_n64(S[(c + 1) & 1], ya[i * 4 + 2 * h], yb[i * 4 + 2 * h], ya[i * 4 + 2 * h + 1],
                              yb[i * 4 + 2 * h + 1],
                              make_desc(w1_base + (c + 1) * 8 * W1_SBO + 2 * t * W1_LBO, W1_LBO, W1_SBO), t != 0);
                }
                wg_commit();
                wg_wait<1>();
            } else {
                wg_wait<0>();
            }
            float(&Sc)[32] = S[c & 1];
#pragma unroll
            for (int j = 0; j < 8; j++) {
                float g0 = gelu2(Sc[4 * j]);
                float g1 = gelu2(Sc[4 * j + 1]);
                float g2 = gelu2(Sc[4 * j + 2]);
                float g3 = gelu2(Sc[4 * j + 3]);
                hf[2 * j] = pack_bf16(g0, g1);
                hf[2 * j + 1] = pack_bf16(g2, g3);
            }
            wg_fence();
#pragma unroll
            for (int t = 0; t < 4; t++) {
                wgmma_n96(O, hf[4 * t], hf[4 * t + 1], hf[4 * t + 2], hf[4 * t + 3],
                          make_desc(w2_base + (c * 8 + 2 * t) * W2_LBO, W2_LBO, W2_SBO), 1);
            }
            wg_commit();
        }
        wg_wait<0>();
        int r0 = tile * TILE_M + warp * 16 + (lane >> 2);
        uint4* p0 = reinterpret_cast<uint4*>(out + (size_t)r0 * C_IN + q * 8);
        uint4* p1 = reinterpret_cast<uint4*>(out + (size_t)(r0 + 8) * C_IN + q * 8);
#pragma unroll
        for (int i = 0; i < 3; i++) {
            uint32_t wa[4] = {xr.a[i].x, xr.a[i].y, xr.a[i].z, xr.a[i].w};
            uint32_t wb[4] = {xr.b[i].x, xr.b[i].y, xr.b[i].z, xr.b[i].w};
            uint32_t oa[4], ob[4];
#pragma unroll
            for (int p = 0; p < 4; p++) {
                int j = i * 4 + p;
                oa[p] = pack_bf16(bf_lo(wa[p]) + O[4 * j], bf_hi(wa[p]) + O[4 * j + 1]);
                ob[p] = pack_bf16(bf_lo(wb[p]) + O[4 * j + 2], bf_hi(wb[p]) + O[4 * j + 3]);
            }
            p0[i * 4] = make_uint4(oa[0], oa[1], oa[2], oa[3]);
            p1[i * 4] = make_uint4(ob[0], ob[1], ob[2], ob[3]);
        }
    }
}

extern "C" void kernel_launch(void* const* d_in, const int* in_sizes, int n_in, void* d_out, int out_size) {
    const __nv_bfloat16* x = (const __nv_bfloat16*)d_in[0];
    const __nv_bfloat16* dw = (const __nv_bfloat16*)d_in[1];
    const __nv_bfloat16* w1 = (const __nv_bfloat16*)d_in[2];
    const __nv_bfloat16* w2 = (const __nv_bfloat16*)d_in[3];
    const __nv_bfloat16* grn_g = (const __nv_bfloat16*)d_in[4];
    const __nv_bfloat16* grn_b = (const __nv_bfloat16*)d_in[5];
    __nv_bfloat16* out = (__nv_bfloat16*)d_out;

    static int n_sm = 0;
    const int smem1 = 73728 + 512 + 1536;
    const int smem2 = 2 * 73728 + 1024 + 1536 + 1536;
    if (n_sm == 0) {
        int dev = 0;
        cudaGetDevice(&dev);
        cudaDeviceGetAttribute(&n_sm, cudaDevAttrMultiProcessorCount, dev);
        if (n_sm > MAX_CTAS) n_sm = MAX_CTAS;
        cudaFuncSetAttribute(k_stats, cudaFuncAttributeMaxDynamicSharedMemorySize, smem1);
        cudaFuncSetAttribute(k_main, cudaFuncAttributeMaxDynamicSharedMemorySize, smem2);
    }
    k_stats<<<n_sm, 256, smem1>>>(x, dw, w1);
    k_main<<<n_sm, 256, smem2>>>(x, dw, w1, w2, grn_g, grn_b, out, n_sm);
}
```

```cpp
#include <cuda_runtime.h>
#include <cuda_bf16.h>
#include <stdint.h>

#define C_IN 96
#define C_H 384
#define NROWS (512 * 512)
#define TILE_M 64
#define NTILES (NROWS / TILE_M)
#define MAX_CTAS 256

__device__ float g_partial[MAX_CTAS * C_H];

__device__ __forceinline__ uint32_t smem_u32(const void* p) {
    return (uint32_t)__cvta_generic_to_shared(p);
}
__device__ __forceinline__ uint64_t make_desc(uint32_t addr, uint32_t lbo, uint32_t sbo) {
    uint64_t d = 0;
    d |= (uint64_t)((addr & 0x3FFFF) >> 4);
    d |= (uint64_t)((lbo >> 4) & 0x3FFF) << 16;
    d |= (uint64_t)((sbo >> 4) & 0x3FFF) << 32;
    return d;
}
__device__ __forceinline__ void wg_fence() { asm volatile("wgmma.fence.sync.aligned;\n" ::: "memory"); }
__device__ __forceinline__ void wg_commit() { asm volatile("wgmma.commit_group.sync.aligned;\n" ::: "memory"); }
template <int N>
__device__ __forceinline__ void wg_wait() { asm volatile("wgmma.wait_group.sync.aligned %0;\n" ::"n"(N) : "memory"); }

__device__ __forceinline__ float tanh_approx(float x) {
    float y;
    asm("tanh.approx.f32 %0, %1;" : "=f"(y) : "f"(x));
    return y;
}
__device__ __forceinline__ uint32_t pack_bf16(float lo, float hi) {
    uint32_t r;
    asm("cvt.rn.bf16x2.f32 %0, %1, %2;" : "=r"(r) : "f"(hi), "f"(lo));
    return r;
}
__device__ __forceinline__ float bf_lo(uint32_t v) { return __uint_as_float(v << 16); }
__device__ __forceinline__ float bf_hi(uint32_t v) { return __uint_as_float(v & 0xffff0000u); }

__device__ __forceinline__ void wgmma_n64(float (&d)[32], uint32_t a0, uint32_t a1, uint32_t a2, uint32_t a3,
                                          uint64_t bdesc, int scale_d) {
    asm volatile(
        "{\n"
        ".reg .pred p;\n"
        "setp.ne.b32 p, %37, 0;\n"
        "wgmma.mma_async.sync.aligned.m64n64k16.f32.bf16.bf16 "
        "{%0, %1, %2, %3, %4, %5, %6, %7, %8, %9, %10, %11, %12, %13, %14, %15, "
        " %16, %17, %18, %19, %20, %21, %22, %23, %24, %25, %26, %27, %28, %29, %30, %31}, "
        "{%32, %33, %34, %35}, %36, p, 1, 1, 1;\n"
        "}\n"
        : "+f"(d[0]), "+f"(d[1]), "+f"(d[2]), "+f"(d[3]), "+f"(d[4]), "+f"(d[5]), "+f"(d[6]), "+f"(d[7]),
          "+f"(d[8]), "+f"(d[9]), "+f"(d[10]), "+f"(d[11]), "+f"(d[12]), "+f"(d[13]), "+f"(d[14]), "+f"(d[15]),
          "+f"(d[16]), "+f"(d[17]), "+f"(d[18]), "+f"(d[19]), "+f"(d[20]), "+f"(d[21]), "+f"(d[22]), "+f"(d[23]),
          "+f"(d[24]), "+f"(d[25]), "+f"(d[26]), "+f"(d[27]), "+f"(d[28]), "+f"(d[29]), "+f"(d[30]), "+f"(d[31])
        : "r"(a0), "r"(a1), "r"(a2), "r"(a3), "l"(bdesc), "r"(scale_d));
}

__device__ __forceinline__ void wgmma_n96(float (&d)[48], uint32_t a0, uint32_t a1, uint32_t a2, uint32_t a3,
                                          uint64_t bdesc, int scale_d) {
    asm volatile(
        "{\n"
        ".reg .pred p;\n"
        "setp.ne.b32 p, %53, 0;\n"
        "wgmma.mma_async.sync.aligned.m64n96k16.f32.bf16.bf16 "
        "{%0, %1, %2, %3, %4, %5, %6, %7, %8, %9, %10, %11, %12, %13, %14, %15, "
        " %16, %17, %18, %19, %20, %21, %22, %23, %24, %25, %26, %27, %28, %29, %30, %31, "
        " %32, %33, %34, %35, %36, %37, %38, %39, %40, %41, %42, %43, %44, %45, %46, %47}, "
        "{%48, %49, %50, %51}, %52, p, 1, 1, 1;\n"
        "}\n"
        : "+f"(d[0]), "+f"(d[1]), "+f"(d[2]), "+f"(d[3]), "+f"(d[4]), "+f"(d[5]), "+f"(d[6]), "+f"(d[7]),
          "+f"(d[8]), "+f"(d[9]), "+f"(d[10]), "+f"(d[11]), "+f"(d[12]), "+f"(d[13]), "+f"(d[14]), "+f"(d[15]),
          "+f"(d[16]), "+f"(d[17]), "+f"(d[18]), "+f"(d[19]), "+f"(d[20]), "+f"(d[21]), "+f"(d[22]), "+f"(d[23]),
          "+f"(d[24]), "+f"(d[25]), "+f"(d[26]), "+f"(d[27]), "+f"(d[28]), "+f"(d[29]), "+f"(d[30]), "+f"(d[31]),
          "+f"(d[32]), "+f"(d[33]), "+f"(d[34]), "+f"(d[35]), "+f"(d[36]), "+f"(d[37]), "+f"(d[38]), "+f"(d[39]),
          "+f"(d[40]), "+f"(d[41]), "+f"(d[42]), "+f"(d[43]), "+f"(d[44]), "+f"(d[45]), "+f"(d[46]), "+f"(d[47])
        : "r"(a0), "r"(a1), "r"(a2), "r"(a3), "l"(bdesc), "r"(scale_d));
}

__device__ __forceinline__ int k1_to_channel(int k) {
    int t = k >> 4, r = k & 15;
    int q = (r & 7) >> 1;
    int e = (r & 1) + ((r >> 3) << 1);
    return 32 * (t >> 1) + 8 * q + 4 * (t & 1) + e;
}
__device__ __forceinline__ int n2_to_channel(int n) {
    int j = n >> 3, r = n & 7;
    int q = r >> 1, e = r & 1;
    return 32 * (j >> 2) + 8 * q + 2 * (j & 3) + e;
}

#define W1_LBO 128
#define W1_SBO (12 * 128)
#define W2_LBO 128
#define W2_SBO (48 * 128)

__device__ __forceinline__ void stage_w1(unsigned char* sm, const __nv_bfloat16* __restrict__ w1, int tid, int nthreads) {
    for (int it = tid; it < 96 * 48; it += nthreads) {
        int kr = it & 7;
        int nb = (it >> 3) % 48;
        int kb = (it >> 3) / 48;
        int ch = k1_to_channel(kb * 8 + kr);
        uint4 v = __ldg(reinterpret_cast<const uint4*>(w1 + ch * C_H + nb * 8));
        *reinterpret_cast<uint4*>(sm + nb * W1_SBO + kb * W1_LBO + kr * 16) = v;
    }
}

struct XRows {
    uint4 a[3];
    uint4 b[3];
};

__device__ __forceinline__ void load_x(XRows& xr, const __nv_bfloat16* __restrict__ x, int tile, int warp, int lane) {
    int r0 = tile * TILE_M + warp * 16 + (lane >> 2);
    const uint4* p0 = reinterpret_cast<const uint4*>(x + (size_t)r0 * C_IN + (lane & 3) * 8);
    const uint4* p1 = reinterpret_cast<const uint4*>(x + (size_t)(r0 + 8) * C_IN + (lane & 3) * 8);
#pragma unroll
    for (int i = 0; i < 3; i++) {
        xr.a[i] = __ldg(p0 + i * 4);
        xr.b[i] = __ldg(p1 + i * 4);
    }
}

__device__ __forceinline__ void ln_row(const uint4 (&xv)[3], const float* __restrict__ dwv, uint32_t (&y)[12]) {
    float d[24];
    float s = 0.f;
#pragma unroll
    for (int i = 0; i < 3; i++) {
        uint32_t w[4] = {xv[i].x, xv[i].y, xv[i].z, xv[i].w};
#pragma unroll
        for (int p = 0; p < 4; p++) {
            d[i * 8 + 2 * p] = bf_lo(w[p]) * dwv[i * 8 + 2 * p];
            d[i * 8 + 2 * p + 1] = bf_hi(w[p]) * dwv[i * 8 + 2 * p + 1];
            s += d[i * 8 + 2 * p] + d[i * 8 + 2 * p + 1];
        }
    }
    s += __shfl_xor_sync(0xffffffffu, s, 1);
    s += __shfl_xor_sync(0xffffffffu, s, 2);
    float mean = s * (1.0f / C_IN);
    float v = 0.f;
#pragma unroll
    for (int i = 0; i < 24; i++) {
        d[i] -= mean;
        v = fmaf(d[i], d[i], v);
    }
    v += __shfl_xor_sync(0xffffffffu, v, 1);
    v += __shfl_xor_sync(0xffffffffu, v, 2);
    float rstd = rsqrtf(v * (1.0f / C_IN) + 1e-5f);
#pragma unroll
    for (int i = 0; i < 12; i++) y[i] = pack_bf16(d[2 * i] * rstd, d[2 * i + 1] * rstd);
}

#define GELU_C0 0.7978845608028654f
#define GELU_C1 (0.7978845608028654f * 0.044715f)

__device__ __forceinline__ float gelu2(float u) {
    float t = u * u;
    float p = fmaf(t, GELU_C1, GELU_C0);
    float a = p * u;
    float th = tanh_approx(a);
    return fmaf(u, th, u);
}

__global__ void __launch_bounds__(256, 1)
k_stats(const __nv_bfloat16* __restrict__ x, const __nv_bfloat16* __restrict__ dw, const __nv_bfloat16* __restrict__ w1) {
    extern __shared__ __align__(1024) unsigned char smem[];
    unsigned char* s_w1 = smem;
    float* s_dw = reinterpret_cast<float*>(smem + 73728);
    float* s_red = reinterpret_cast<float*>(smem + 73728 + 512);

    const int tid = threadIdx.x;
    const int wg = tid >> 7;
    const int warp = (tid >> 5) & 3;
    const int lane = tid & 31;
    const int q = lane & 3;

    stage_w1(s_w1, w1, tid, 256);
    if (tid < C_IN) s_dw[tid] = __bfloat162float(dw[tid]);
    for (int i = tid; i < C_H; i += 256) s_red[i] = 0.f;
    asm volatile("fence.proxy.async.shared::cta;\n" ::: "memory");
    __syncthreads();

    float dwv[24];
#pragma unroll
    for (int i = 0; i < 3; i++)
#pragma unroll
        for (int p = 0; p < 8; p++) dwv[i * 8 + p] = s_dw[32 * i + 8 * q + p];

    float ss[96];
#pragma unroll
    for (int i = 0; i < 96; i++) ss[i] = 0.f;

    const uint32_t w1_base = smem_u32(s_w1);
    const int nwg = gridDim.x * 2;
    int tile = blockIdx.x * 2 + wg;
    XRows xr;
    if (tile < NTILES) load_x(xr, x, tile, warp, lane);
    for (; tile < NTILES; tile += nwg) {
        uint32_t ya[12], yb[12];
        ln_row(xr.a, dwv, ya);
        ln_row(xr.b, dwv, yb);
        int ntile = tile + nwg;
        if (ntile < NTILES) load_x(xr, x, ntile, warp, lane);

        float S[2][32];
        wg_fence();
#pragma unroll
        for (int t = 0; t < 6; t++) {
            int i = t >> 1, h = t & 1;
            wgmma_n64(S[0], ya[i * 4 + 2 * h], yb[i * 4 + 2 * h], ya[i * 4 + 2 * h + 1], yb[i * 4 + 2 * h + 1],
                      make_desc(w1_base + 2 * t * W1_LBO, W1_LBO, W1_SBO), t != 0);
        }
        wg_commit();
#pragma unroll
        for (int c = 0; c < 6; c++) {
            if (c + 1 < 6) {
                wg_fence();
#pragma unroll
                for (int t = 0; t < 6; t++) {
                    int i = t >> 1, h = t & 1;
                    wgmma_n64(S[(c + 1) & 1], ya[i * 4 + 2 * h], yb[i * 4 + 2 * h], ya[i * 4 + 2 * h + 1],
                              yb[i * 4 + 2 * h + 1],
                              make_desc(w1_base + (c + 1) * 8 * W1_SBO + 2 * t * W1_LBO, W1_LBO, W1_SBO), t != 0);
                }
                wg_commit();
                wg_wait<1>();
            } else {
                wg_wait<0>();
            }
            float(&Sc)[32] = S[c & 1];
#pragma unroll
            for (int j = 0; j < 8; j++) {
                float g0 = gelu2(Sc[4 * j]);
                float g1 = gelu2(Sc[4 * j + 1]);
                float g2 = gelu2(Sc[4 * j + 2]);
                float g3 = gelu2(Sc[4 * j + 3]);
                ss[c * 16 + 2 * j] = fmaf(g0, g0, fmaf(g2, g2, ss[c * 16 + 2 * j]));
                ss[c * 16 + 2 * j + 1] = fmaf(g1, g1, fmaf(g3, g3, ss[c * 16 + 2 * j + 1]));
            }
        }
    }
#pragma unroll
    for (int i = 0; i < 96; i++) {
        float v = ss[i];
        v += __shfl_xor_sync(0xffffffffu, v, 4);
        v += __shfl_xor_sync(0xffffffffu, v, 8);
        v += __shfl_xor_sync(0xffffffffu, v, 16);
        if (lane < 4) {
            int c = i >> 4, j = (i >> 1) & 7, e = i & 1;
            atomicAdd(&s_red[c * 64 + 8 * j + 2 * q + e], v);
        }
    }
    __syncthreads();
    for (int i = tid; i < C_H; i += 256) g_partial[blockIdx.x * C_H + i] = s_red[i] * 0.25f;
}

__global__ void __launch_bounds__(256, 1)
k_main(const __nv_bfloat16* __restrict__ x, const __nv_bfloat16* __restrict__ dw, const __nv_bfloat16* __restrict__ w1,
       const __nv_bfloat16* __restrict__ w2, const __nv_bfloat16* __restrict__ grn_g,
       const __nv_bfloat16* __restrict__ grn_b, __nv_bfloat16* __restrict__ out, int n_part) {
    extern __shared__ __align__(1024) unsigned char smem[];
    unsigned char* s_w1 = smem;
    unsigned char* s_w2 = smem + 73728;
    float* s_dw = reinterpret_cast<float*>(smem + 2 * 73728);
    float* s_c = reinterpret_cast<float*>(smem + 2 * 73728 + 512);
    float* s_s = reinterpret_cast<float*>(smem + 2 * 73728 + 1024);
    float* s_tmp = reinterpret_cast<float*>(smem + 2 * 73728 + 1024 + 1536);

    const int tid = threadIdx.x;
    const int wg = tid >> 7;
    const int warp = (tid >> 5) & 3;
    const int lane = tid & 31;
    const int q = lane & 3;

    stage_w1(s_w1, w1, tid, 256);
    if (tid < C_IN) { s_dw[tid] = __bfloat162float(dw[tid]); s_c[tid] = 0.f; }
    float lsum = 0.f;
    for (int k = tid; k < C_H; k += 256) {
        float a = 0.f;
        for (int b = 0; b < n_part; b++) a += g_partial[b * C_H + k];
        float gx = sqrtf(a + 1e-6f);
        s_s[k] = gx;
        lsum += gx;
    }
#pragma unroll
    for (int o = 16; o > 0; o >>= 1) lsum += __shfl_xor_sync(0xffffffffu, lsum, o);
    if (lane == 0) s_tmp[tid >> 5] = lsum;
    __syncthreads();
    float tot = 0.f;
#pragma unroll
    for (int i = 0; i < 8; i++) tot += s_tmp[i];
    float inv = 1.0f / (tot * (1.0f / C_H) + 1e-6f);
    __syncthreads();
    for (int k = tid; k < C_H; k += 256) {
        float nx = s_s[k] * inv;
        s_s[k] = 0.5f * (1.0f + __bfloat162float(grn_g[k]) * nx);
    }
    {
        float a0 = 0.f, a1 = 0.f, a2 = 0.f;
        int kbase = (tid >> 5) * 48;
#pragma unroll 8
        for (int k = kbase; k < kbase + 48; k++) {
            float b = __bfloat162float(grn_b[k]);
            a0 = fmaf(b, __bfloat162float(w2[k * C_IN + lane]), a0);
            a1 = fmaf(b, __bfloat162float(w2[k * C_IN + lane + 32]), a1);
            a2 = fmaf(b, __bfloat162float(w2[k * C_IN + lane + 64]), a2);
        }
        atomicAdd(&s_c[lane], a0);
        atomicAdd(&s_c[lane + 32], a1);
        atomicAdd(&s_c[lane + 64], a2);
    }
    __syncthreads();
    for (int it = tid; it < 384 * 3; it += 256) {
        int kr = it & 7;
        int grp = (it >> 3) % 3;
        int kb = (it >> 3) / 3;
        int k = kb * 8 + kr;
        float sk = s_s[k];
        const uint4* src = reinterpret_cast<const uint4*>(w2 + k * C_IN + grp * 32);
        uint32_t wv[4][4];
#pragma unroll
        for (int qq = 0; qq < 4; qq++) {
            uint4 v = __ldg(src + qq);
            wv[qq][0] = v.x; wv[qq][1] = v.y; wv[qq][2] = v.z; wv[qq][3] = v.w;
        }
#pragma unroll
        for (int jj = 0; jj < 4; jj++) {
            uint32_t o[4];
#pragma unroll
            for (int qq = 0; qq < 4; qq++) o[qq] = pack_bf16(sk * bf_lo(wv[qq][jj]), sk * bf_hi(wv[qq][jj]));
            *reinterpret_cast<uint4*>(s_w2 + (grp * 4 + jj) * W2_SBO + kb * W2_LBO + kr * 16) = make_uint4(o[0], o[1], o[2], o[3]);
        }
    }
    asm volatile("fence.proxy.async.shared::cta;\n" ::: "memory");
    __syncthreads();

    float dwv[24];
#pragma unroll
    for (int i = 0; i < 3; i++)
#pragma unroll
        for (int p = 0; p < 8; p++) dwv[i * 8 + p] = s_dw[32 * i + 8 * q + p];

    const uint32_t w1_base = smem_u32(s_w1);
    const uint32_t w2_base = smem_u32(s_w2);
    const int nwg = gridDim.x * 2;
    int tile = blockIdx.x * 2 + wg;
    XRows xr, xn;
    if (tile < NTILES) load_x(xn, x, tile, warp, lane);
    for (; tile < NTILES; tile += nwg) {
        xr = xn;
        uint32_t ya[12], yb[12];
        ln_row(xr.a, dwv, ya);
        ln_row(xr.b, dwv, yb);
        int ntile = tile + nwg;
        if (ntile < NTILES) load_x(xn, x, ntile, warp, lane);

        float O[48];
#pragma unroll
        for (int j = 0; j < 12; j++) {
            float c0 = s_c[32 * (j >> 2) + 8 * q + 2 * (j & 3)];
            float c1 = s_c[32 * (j >> 2) + 8 * q + 2 * (j & 3) + 1];
            O[4 * j] = c0; O[4 * j + 1] = c1; O[4 * j + 2] = c0; O[4 * j + 3] = c1;
        }
        float S[2][32];
        uint32_t hf[16];
        wg_fence();
#pragma unroll
        for (int t = 0; t < 6; t++) {
            int i = t >> 1, h = t & 1;
            wgmma_n64(S[0], ya[i * 4 + 2 * h], yb[i * 4 + 2 * h], ya[i * 4 + 2 * h + 1], yb[i * 4 + 2 * h + 1],
                      make_desc(w1_base + 2 * t * W1_LBO, W1_LBO, W1_SBO), t != 0);
        }
        wg_commit();
#pragma unroll
        for (int c = 0; c < 6; c++) {
            if (c + 1 < 6) {
                wg_fence();
#pragma unroll
                for (int t = 0; t < 6; t++) {
                    int i = t >> 1, h = t & 1;
                    wgmma_n64(S[(c + 1) & 1], ya[i * 4 + 2 * h], yb[i * 4 + 2 * h], ya[i * 4 + 2 * h + 1],
                              yb[i * 4 + 2 * h + 1],
                              make_desc(w1_base + (c + 1) * 8 * W1_SBO + 2 * t * W1_LBO, W1_LBO, W1_SBO), t != 0);
                }
                wg_commit();
                wg_wait<1>();
            } else {
                wg_wait<0>();
            }
            float(&Sc)[32] = S[c & 1];
#pragma unroll
            for (int j = 0; j < 8; j++) {
                float g0 = gelu2(Sc[4 * j]);
                float g1 = gelu2(Sc[4 * j + 1]);
                float g2 = gelu2(Sc[4 * j + 2]);
                float g3 = gelu2(Sc[4 * j + 3]);
                hf[2 * j] = pack_bf16(g0, g1);
                hf[2 * j + 1] = pack_bf16(g2, g3);
            }
            wg_fence();
#pragma unroll
            for (int t = 0; t < 4; t++) {
                wgmma_n96(O, hf[4 * t], hf[4 * t + 1], hf[4 * t + 2], hf[4 * t + 3],
                          make_desc(w2_base + (c * 8 + 2 * t) * W2_LBO, W2_LBO, W2_SBO), 1);
            }
            wg_commit();
        }
        wg_wait<0>();
        int r0 = tile * TILE_M + warp * 16 + (lane >> 2);
        uint4* p0 = reinterpret_cast<uint4*>(out + (size_t)r0 * C_IN + q * 8);
        uint4* p1 = reinterpret_cast<uint4*>(out + (size_t)(r0 + 8) * C_IN + q * 8);
#pragma unroll
        for (int i = 0; i < 3; i++) {
            uint32_t wa[4] = {xr.a[i].x, xr.a[i].y, xr.a[i].z, xr.a[i].w};
            uint32_t wb[4] = {xr.b[i].x, xr.b[i].y, xr.b[i].z, xr.b[i].w};
            uint32_t oa[4], ob[4];
#pragma unroll
            for (int p = 0; p < 4; p++) {
                int j = i * 4 + p;
                oa[p] = pack_bf16(bf_lo(wa[p]) + O[4 * j], bf_hi(wa[p]) + O[4 * j + 1]);
                ob[p] = pack_bf16(bf_lo(wb[p]) + O[4 * j + 2], bf_hi(wb[p]) + O[4 * j + 3]);
            }
            p0[i * 4] = make_uint4(oa[0], oa[1], oa[2], oa[3]);
            p1[i * 4] = make_uint4(ob[0], ob[1], ob[2], ob[3]);
        }
    }
}

extern "C" void kernel_launch(void* const* d_in, const int* in_sizes, int n_in, void* d_out, int out_size) {
    const __nv_bfloat16* x = (const __nv_bfloat16*)d_in[0];
    const __nv_bfloat16* dw = (const __nv_bfloat16*)d_in[1];
    const __nv_bfloat16* w1 = (const __nv_bfloat16*)d_in[2];
    const __nv_bfloat16* w2 = (const __nv_bfloat16*)d_in[3];
    const __nv_bfloat16* grn_g = (const __nv_bfloat16*)d_in[4];
    const __nv_bfloat16* grn_b = (const __nv_bfloat16*)d_in[5];
    __nv_bfloat16* out = (__nv_bfloat16*)d_out;

    static int n_sm = 0;
    const int smem1 = 73728 + 512 + 1536;
    const int smem2 = 2 * 73728 + 1024 + 1536 + 1536;
    if (n_sm == 0) {
        int dev = 0;
        cudaGetDevice(&dev);
        cudaDeviceGetAttribute(&n_sm, cudaDevAttrMultiProcessorCount, dev);
        if (n_sm > MAX_CTAS) n_sm = MAX_CTAS;
        cudaFuncSetAttribute(k_stats, cudaFuncAttributeMaxDynamicSharedMemorySize, smem1);
        cudaFuncSetAttribute(k_main, cudaFuncAttributeMaxDynamicSharedMemorySize, smem2);
    }
    k_stats<<<n_sm, 256, smem1>>>(x, dw, w1);
    k_main<<<n_sm, 256, smem2>>>(x, dw, w1, w2, grn_g, grn_b, out, n_sm);
}
```

```cpp
#include <cuda_runtime.h>
#include <cuda_bf16.h>
#include <stdint.h>

#define C_IN 96
#define C_H 384
#define NROWS (512 * 512)
#define TILE_M 64
#define NTILES (NROWS / TILE_M)
#define MAX_CTAS 256

__device__ float g_partial[MAX_CTAS * C_H];

__device__ __forceinline__ uint32_t smem_u32(const void* p) {
    return (uint32_t)__cvta_generic_to_shared(p);
}
__device__ __forceinline__ uint64_t make_desc(uint32_t addr, uint32_t lbo, uint32_t sbo) {
    uint64_t d = 0;
    d |= (uint64_t)((addr & 0x3FFFF) >> 4);
    d |= (uint64_t)((lbo >> 4) & 0x3FFF) << 16;
    d |= (uint64_t)((sbo >> 4) & 0x3FFF) << 32;
    return d;
}
__device__ __forceinline__ void wg_fence() { asm volatile("wgmma.fence.sync.aligned;\n" ::: "memory"); }
__device__ __forceinline__ void wg_commit() { asm volatile("wgmma.commit_group.sync.aligned;\n" ::: "memory"); }
template <int N>
__device__ __forceinline__ void wg_wait() { asm volatile("wgmma.wait_group.sync.aligned %0;\n" ::"n"(N) : "memory"); }

__device__ __forceinline__ float tanh_approx(float x) {
    float y;
    asm("tanh.approx.f32 %0, %1;" : "=f"(y) : "f"(x));
    return y;
}
__device__ __forceinline__ uint32_t pack_bf16(float lo, float hi) {
    uint32_t r;
    asm("cvt.rn.bf16x2.f32 %0, %1, %2;" : "=r"(r) : "f"(hi), "f"(lo));
    return r;
}
__device__ __forceinline__ float bf_lo(uint32_t v) { return __uint_as_float(v << 16); }
__device__ __forceinline__ float bf_hi(uint32_t v) { return __uint_as_float(v & 0xffff0000u); }

__device__ __forceinline__ void wgmma_n64(float (&d)[32], uint32_t a0, uint32_t a1, uint32_t a2, uint32_t a3,
                                          uint64_t bdesc, int scale_d) {
    asm volatile(
        "{\n"
        ".reg .pred p;\n"
        "setp.ne.b32 p, %37, 0;\n"
        "wgmma.mma_async.sync.aligned.m64n64k16.f32.bf16.bf16 "
        "{%0, %1, %2, %3, %4, %5, %6, %7, %8, %9, %10, %11, %12, %13, %14, %15, "
        " %16, %17, %18, %19, %20, %21, %22, %23, %24, %25, %26, %27, %28, %29, %30, %31}, "
        "{%32, %33, %34, %35}, %36, p, 1, 1, 1;\n"
        "}\n"
        : "+f"(d[0]), "+f"(d[1]), "+f"(d[2]), "+f"(d[3]), "+f"(d[4]), "+f"(d[5]), "+f"(d[6]), "+f"(d[7]),
          "+f"(d[8]), "+f"(d[9]), "+f"(d[10]), "+f"(d[11]), "+f"(d[12]), "+f"(d[13]), "+f"(d[14]), "+f"(d[15]),
          "+f"(d[16]), "+f"(d[17]), "+f"(d[18]), "+f"(d[19]), "+f"(d[20]), "+f"(d[21]), "+f"(d[22]), "+f"(d[23]),
          "+f"(d[24]), "+f"(d[25]), "+f"(d[26]), "+f"(d[27]), "+f"(d[28]), "+f"(d[29]), "+f"(d[30]), "+f"(d[31])
        : "r"(a0), "r"(a1), "r"(a2), "r"(a3), "l"(bdesc), "r"(scale_d));
}

__device__ __forceinline__ void wgmma_n96(float (&d)[48], uint32_t a0, uint32_t a1, uint32_t a2, uint32_t a3,
                                          uint64_t bdesc, int scale_d) {
    asm volatile(
        "{\n"
        ".reg .pred p;\n"
        "setp.ne.b32 p, %53, 0;\n"
        "wgmma.mma_async.sync.aligned.m64n96k16.f32.bf16.bf16 "
        "{%0, %1, %2, %3, %4, %5, %6, %7, %8, %9, %10, %11, %12, %13, %14, %15, "
        " %16, %17, %18, %19, %20, %21, %22, %23, %24, %25, %26, %27, %28, %29, %30, %31, "
        " %32, %33, %34, %35, %36, %37, %38, %39, %40, %41, %42, %43, %44, %45, %46, %47}, "
        "{%48, %49, %50, %51}, %52, p, 1, 1, 1;\n"
        "}\n"
        : "+f"(d[0]), "+f"(d[1]), "+f"(d[2]), "+f"(d[3]), "+f"(d[4]), "+f"(d[5]), "+f"(d[6]), "+f"(d[7]),
          "+f"(d[8]), "+f"(d[9]), "+f"(d[10]), "+f"(d[11]), "+f"(d[12]), "+f"(d[13]), "+f"(d[14]), "+f"(d[15]),
          "+f"(d[16]), "+f"(d[17]), "+f"(d[18]), "+f"(d[19]), "+f"(d[20]), "+f"(d[21]), "+f"(d[22]), "+f"(d[23]),
          "+f"(d[24]), "+f"(d[25]), "+f"(d[26]), "+f"(d[27]), "+f"(d[28]), "+f"(d[29]), "+f"(d[30]), "+f"(d[31]),
          "+f"(d[32]), "+f"(d[33]), "+f"(d[34]), "+f"(d[35]), "+f"(d[36]), "+f"(d[37]), "+f"(d[38]), "+f"(d[39]),
          "+f"(d[40]), "+f"(d[41]), "+f"(d[42]), "+f"(d[43]), "+f"(d[44]), "+f"(d[45]), "+f"(d[46]), "+f"(d[47])
        : "r"(a0), "r"(a1), "r"(a2), "r"(a3), "l"(bdesc), "r"(scale_d));
}

__device__ __forceinline__ int k1_to_channel(int k) {
    int t = k >> 4, r = k & 15;
    int q = (r & 7) >> 1;
    int e = (r & 1) + ((r >> 3) << 1);
    return 32 * (t >> 1) + 8 * q + 4 * (t & 1) + e;
}
__device__ __forceinline__ int n2_to_channel(int n) {
    int j = n >> 3, r = n & 7;
    int q = r >> 1, e = r & 1;
    return 32 * (j >> 2) + 8 * q + 2 * (j & 3) + e;
}

#define W1_LBO 128
#define W1_SBO (12 * 128)
#define W2_LBO 128
#define W2_SBO (48 * 128)

__device__ __forceinline__ void stage_w1(unsigned char* sm, const __nv_bfloat16* __restrict__ w1, int tid, int nthreads) {
    for (int it = tid; it < 96 * 48; it += nthreads) {
        int kr = it & 7;
        int nb = (it >> 3) % 48;
        int kb = (it >> 3) / 48;
        int ch = k1_to_channel(kb * 8 + kr);
        uint4 v = __ldg(reinterpret_cast<const uint4*>(w1 + ch * C_H + nb * 8));
        *reinterpret_cast<uint4*>(sm + nb * W1_SBO + kb * W1_LBO + kr * 16) = v;
    }
}

struct XRows {
    uint4 a[3];
    uint4 b[3];
};

__device__ __forceinline__ void load_x(XRows& xr, const __nv_bfloat16* __restrict__ x, int tile, int warp, int lane) {
    int r0 = tile * TILE_M + warp * 16 + (lane >> 2);
    const uint4* p0 = reinterpret_cast<const uint4*>(x + (size_t)r0 * C_IN + (lane & 3) * 8);
    const uint4* p1 = reinterpret_cast<const uint4*>(x + (size_t)(r0 + 8) * C_IN + (lane & 3) * 8);
#pragma unroll
    for (int i = 0; i < 3; i++) {
        xr.a[i] = __ldg(p0 + i * 4);
        xr.b[i] = __ldg(p1 + i * 4);
    }
}

__device__ __forceinline__ void ln_row(const uint4 (&xv)[3], const float* __restrict__ dwv, uint32_t (&y)[12]) {
    float d[24];
    float s = 0.f;
#pragma unroll
    for (int i = 0; i < 3; i++) {
        uint32_t w[4] = {xv[i].x, xv[i].y, xv[i].z, xv[i].w};
#pragma unroll
        for (int p = 0; p < 4; p++) {
            d[i * 8 + 2 * p] = bf_lo(w[p]) * dwv[i * 8 + 2 * p];
            d[i * 8 + 2 * p + 1] = bf_hi(w[p]) * dwv[i * 8 + 2 * p + 1];
            s += d[i * 8 + 2 * p] + d[i * 8 + 2 * p + 1];
        }
    }
    s += __shfl_xor_sync(0xffffffffu, s, 1);
    s += __shfl_xor_sync(0xffffffffu, s, 2);
    float mean = s * (1.0f / C_IN);
    float v = 0.f;
#pragma unroll
    for (int i = 0; i < 24; i++) {
        d[i] -= mean;
        v = fmaf(d[i], d[i], v);
    }
    v += __shfl_xor_sync(0xffffffffu, v, 1);
    v += __shfl_xor_sync(0xffffffffu, v, 2);
    float rstd = rsqrtf(v * (1.0f / C_IN) + 1e-5f);
#pragma unroll
    for (int i = 0; i < 12; i++) y[i] = pack_bf16(d[2 * i] * rstd, d[2 * i + 1] * rstd);
}

#define GELU_C0 0.7978845608028654f
#define GELU_C1 (0.7978845608028654f * 0.044715f)

__device__ __forceinline__ float gelu2(float u) {
    float t = u * u;
    float p = fmaf(t, GELU_C1, GELU_C0);
    float a = p * u;
    float th = tanh_approx(a);
    return fmaf(u, th, u);
}


__device__ __forceinline__ void wgmma_ss_n128_tA(float (&d)[64], uint64_t adesc, uint64_t bdesc, int scale_d) {
    asm volatile(
        "{\n"
        ".reg .pred p;\n"
        "setp.ne.b32 p, %66, 0;\n"
        "wgmma.mma_async.sync.aligned.m64n128k16.f32.bf16.bf16 "
        "{%0, %1, %2, %3, %4, %5, %6, %7, %8, %9, %10, %11, %12, %13, %14, %15, "
        " %16, %17, %18, %19, %20, %21, %22, %23, %24, %25, %26, %27, %28, %29, %30, %31, "
        " %32, %33, %34, %35, %36, %37, %38, %39, %40, %41, %42, %43, %44, %45, %46, %47, "
        " %48, %49, %50, %51, %52, %53, %54, %55, %56, %57, %58, %59, %60, %61, %62, %63}, "
        "%64, %65, p, 1, 1, 1, 0;\n"
        "}\n"
        : "+f"(d[0]), "+f"(d[1]), "+f"(d[2]), "+f"(d[3]), "+f"(d[4]), "+f"(d[5]), "+f"(d[6]), "+f"(d[7]),
          "+f"(d[8]), "+f"(d[9]), "+f"(d[10]), "+f"(d[11]), "+f"(d[12]), "+f"(d[13]), "+f"(d[14]), "+f"(d[15]),
          "+f"(d[16]), "+f"(d[17]), "+f"(d[18]), "+f"(d[19]), "+f"(d[20]), "+f"(d[21]), "+f"(d[22]), "+f"(d[23]),
          "+f"(d[24]), "+f"(d[25]), "+f"(d[26]), "+f"(d[27]), "+f"(d[28]), "+f"(d[29]), "+f"(d[30]), "+f"(d[31]),
          "+f"(d[32]), "+f"(d[33]), "+f"(d[34]), "+f"(d[35]), "+f"(d[36]), "+f"(d[37]), "+f"(d[38]), "+f"(d[39]),
          "+f"(d[40]), "+f"(d[41]), "+f"(d[42]), "+f"(d[43]), "+f"(d[44]), "+f"(d[45]), "+f"(d[46]), "+f"(d[47]),
          "+f"(d[48]), "+f"(d[49]), "+f"(d[50]), "+f"(d[51]), "+f"(d[52]), "+f"(d[53]), "+f"(d[54]), "+f"(d[55]),
          "+f"(d[56]), "+f"(d[57]), "+f"(d[58]), "+f"(d[59]), "+f"(d[60]), "+f"(d[61]), "+f"(d[62]), "+f"(d[63])
        : "l"(adesc), "l"(bdesc), "r"(scale_d));
}
__device__ __forceinline__ void wgmma_ss_n64(float (&d)[32], uint64_t adesc, uint64_t bdesc, int scale_d) {
    asm volatile(
        "{\n"
        ".reg .pred p;\n"
        "setp.ne.b32 p, %34, 0;\n"
        "wgmma.mma_async.sync.aligned.m64n64k16.f32.bf16.bf16 "
        "{%0, %1, %2, %3, %4, %5, %6, %7, %8, %9, %10, %11, %12, %13, %14, %15, "
        " %16, %17, %18, %19, %20, %21, %22, %23, %24, %25, %26, %27, %28, %29, %30, %31}, "
        "%32, %33, p, 1, 1, 0, 1;\n"
        "}\n"
        : "+f"(d[0]), "+f"(d[1]), "+f"(d[2]), "+f"(d[3]), "+f"(d[4]), "+f"(d[5]), "+f"(d[6]), "+f"(d[7]),
          "+f"(d[8]), "+f"(d[9]), "+f"(d[10]), "+f"(d[11]), "+f"(d[12]), "+f"(d[13]), "+f"(d[14]), "+f"(d[15]),
          "+f"(d[16]), "+f"(d[17]), "+f"(d[18]), "+f"(d[19]), "+f"(d[20]), "+f"(d[21]), "+f"(d[22]), "+f"(d[23]),
          "+f"(d[24]), "+f"(d[25]), "+f"(d[26]), "+f"(d[27]), "+f"(d[28]), "+f"(d[29]), "+f"(d[30]), "+f"(d[31])
        : "l"(adesc), "l"(bdesc), "r"(scale_d));
}
__device__ __forceinline__ void wg_bar(int id) { asm volatile("bar.sync %0, 128;" ::"r"(id) : "memory"); }
__device__ __forceinline__ void proxy_fence() { asm volatile("fence.proxy.async.shared::cta;\n" ::: "memory"); }

__device__ __forceinline__ void ln_row4(const uint4 (&xv)[3], const float* __restrict__ s_dwq, uint4 (&y)[3]) {
    float d[24];
    float s = 0.f;
#pragma unroll
    for (int i = 0; i < 3; i++) {
        uint32_t w[4] = {xv[i].x, xv[i].y, xv[i].z, xv[i].w};
        float4 da = *reinterpret_cast<const float4*>(s_dwq + 32 * i);
        float4 db = *reinterpret_cast<const float4*>(s_dwq + 32 * i + 4);
        d[i * 8 + 0] = bf_lo(w[0]) * da.x; d[i * 8 + 1] = bf_hi(w[0]) * da.y;
        d[i * 8 + 2] = bf_lo(w[1]) * da.z; d[i * 8 + 3] = bf_hi(w[1]) * da.w;
        d[i * 8 + 4] = bf_lo(w[2]) * db.x; d[i * 8 + 5] = bf_hi(w[2]) * db.y;
        d[i * 8 + 6] = bf_lo(w[3]) * db.z; d[i * 8 + 7] = bf_hi(w[3]) * db.w;
#pragma unroll
        for (int p = 0; p < 8; p++) s += d[i * 8 + p];
    }
    s += __shfl_xor_sync(0xffffffffu, s, 1);
    s += __shfl_xor_sync(0xffffffffu, s, 2);
    float mean = s * (1.0f / C_IN);
    float v = 0.f;
#pragma unroll
    for (int i = 0; i < 24; i++) {
        d[i] -= mean;
        v = fmaf(d[i], d[i], v);
    }
    v += __shfl_xor_sync(0xffffffffu, v, 1);
    v += __shfl_xor_sync(0xffffffffu, v, 2);
    float rstd = rsqrtf(v * (1.0f / C_IN) + 1e-5f);
#pragma unroll
    for (int i = 0; i < 3; i++) {
        y[i].x = pack_bf16(d[i * 8 + 0] * rstd, d[i * 8 + 1] * rstd);
        y[i].y = pack_bf16(d[i * 8 + 2] * rstd, d[i * 8 + 3] * rstd);
        y[i].z = pack_bf16(d[i * 8 + 4] * rstd, d[i * 8 + 5] * rstd);
        y[i].w = pack_bf16(d[i * 8 + 6] * rstd, d[i * 8 + 7] * rstd);
    }
}

__device__ __forceinline__ void stage_w1n(unsigned char* sm, const __nv_bfloat16* __restrict__ w1, int tid, int nthreads) {
    for (int it = tid; it < 96 * 48; it += nthreads) {
        int kr = it & 7;
        int nb = (it >> 3) % 48;
        int kb = (it >> 3) / 48;
        int ch = kb * 8 + kr;
        uint4 v = __ldg(reinterpret_cast<const uint4*>(w1 + ch * C_H + nb * 8));
        *reinterpret_cast<uint4*>(sm + nb * W1_SBO + kb * W1_LBO + kr * 16) = v;
    }
}

#define Y_LBO 128
#define Y_SBO (12 * 128)

#define NWG 4
#define NTHR (NWG * 128)
#define P1_ROWS 128
#define P1_TILES (NROWS / P1_ROWS)

__global__ void __launch_bounds__(NTHR, 1)
k_stats(const __nv_bfloat16* __restrict__ x, const __nv_bfloat16* __restrict__ dw, const __nv_bfloat16* __restrict__ w1) {
    extern __shared__ __align__(1024) unsigned char smem[];
    unsigned char* s_w1 = smem;
    unsigned char* s_y = smem + 73728;
    float* s_dw = reinterpret_cast<float*>(smem + 73728 + NWG * 24576);
    float* s_red = s_dw + 128;

    const int tid = threadIdx.x;
    const int wg = tid >> 7;
    const int warp = (tid >> 5) & 3;
    const int lane = tid & 31;
    const int q = lane & 3;

    stage_w1n(s_w1, w1, tid, NTHR);
    if (tid < C_IN) s_dw[tid] = __bfloat162float(dw[tid]);
    for (int i = tid; i < C_H; i += NTHR) s_red[i] = 0.f;
    proxy_fence();
    __syncthreads();

    float ss[12];
#pragma unroll
    for (int i = 0; i < 12; i++) ss[i] = 0.f;

    unsigned char* ytile = s_y + wg * 24576;
    const uint32_t w1_base = smem_u32(s_w1);
    const uint32_t y_base = smem_u32(ytile);
    const int nwg = gridDim.x * NWG;
    for (int tile = blockIdx.x * NWG + wg; tile < P1_TILES; tile += nwg) {
#pragma unroll
        for (int it = 0; it < 4; it++) {
            int rl = warp * 32 + it * 8 + (lane >> 2);
            const uint4* p = reinterpret_cast<const uint4*>(x + ((size_t)tile * P1_ROWS + rl) * C_IN + q * 8);
            uint4 xv[3], y[3];
#pragma unroll
            for (int i = 0; i < 3; i++) xv[i] = __ldg(p + i * 4);
            ln_row4(xv, s_dw + 8 * q, y);
#pragma unroll
            for (int i = 0; i < 3; i++)
                *reinterpret_cast<uint4*>(ytile + (rl >> 3) * Y_SBO + (q + 4 * i) * Y_LBO + (rl & 7) * 16) = y[i];
        }
        proxy_fence();
        wg_bar(1 + wg);
#pragma unroll
        for (int m = 0; m < 6; m++) {
            float S[64];
            wg_fence();
#pragma unroll
            for (int t = 0; t < 6; t++) {
                wgmma_ss_n128_tA(S, make_desc(w1_base + m * 8 * W1_SBO + 2 * t * W1_LBO, W1_LBO, W1_SBO),
                                 make_desc(y_base + 2 * t * Y_LBO, Y_LBO, Y_SBO), t != 0);
            }
            wg_commit();
            wg_wait<0>();
            float a0 = ss[2 * m], a1 = ss[2 * m + 1];
#pragma unroll
            for (int j = 0; j < 16; j++) {
                float g0 = gelu2(S[4 * j]);
                float g1 = gelu2(S[4 * j + 1]);
                float g2 = gelu2(S[4 * j + 2]);
                float g3 = gelu2(S[4 * j + 3]);
                a0 = fmaf(g0, g0, a0);
                a1 = fmaf(g2, g2, a1);
                a0 = fmaf(g1, g1, a0);
                a1 = fmaf(g3, g3, a1);
            }
            ss[2 * m] = a0;
            ss[2 * m + 1] = a1;
        }
        wg_bar(1 + wg);
    }
#pragma unroll
    for (int i = 0; i < 12; i++) {
        float v = ss[i];
        v += __shfl_xor_sync(0xffffffffu, v, 1);
        v += __shfl_xor_sync(0xffffffffu, v, 2);
        if (q == 0) {
            int m = i >> 1, hh = i & 1;
            atomicAdd(&s_red[m * 64 + warp * 16 + hh * 8 + (lane >> 2)], v);
        }
    }
    __syncthreads();
    for (int i = tid; i < C_H; i += NTHR) g_partial[blockIdx.x * C_H + i] = s_red[i] * 0.25f;
}

__global__ void __launch_bounds__(NTHR, 1)
k_main(const __nv_bfloat16* __restrict__ x, const __nv_bfloat16* __restrict__ dw, const __nv_bfloat16* __restrict__ w1,
       const __nv_bfloat16* __restrict__ w2, const __nv_bfloat16* __restrict__ grn_g,
       const __nv_bfloat16* __restrict__ grn_b, __nv_bfloat16* __restrict__ out, int n_part) {
    extern __shared__ __align__(1024) unsigned char smem[];
    unsigned char* s_w1 = smem;
    unsigned char* s_w2 = smem + 73728;
    unsigned char* s_y = smem + 2 * 73728;
    float* s_dw = reinterpret_cast<float*>(smem + 2 * 73728 + NWG * 12288);
    float* s_c = s_dw + 128;
    float* s_s = s_c + 128;
    float* s_tmp = s_s + 384;

    const int tid = threadIdx.x;
    const int wg = tid >> 7;
    const int warp = (tid >> 5) & 3;
    const int lane = tid & 31;
    const int q = lane & 3;

    stage_w1n(s_w1, w1, tid, NTHR);
    if (tid < C_IN) { s_dw[tid] = __bfloat162float(dw[tid]); s_c[tid] = 0.f; }
    float lsum = 0.f;
    for (int k = tid; k < C_H; k += NTHR) {
        float a = 0.f;
        for (int b = 0; b < n_part; b++) a += g_partial[b * C_H + k];
        float gx = sqrtf(a + 1e-6f);
        s_s[k] = gx;
        lsum += gx;
    }
#pragma unroll
    for (int o = 16; o > 0; o >>= 1) lsum += __shfl_xor_sync(0xffffffffu, lsum, o);
    if (lane == 0) s_tmp[tid >> 5] = lsum;
    __syncthreads();
    float tot = 0.f;
#pragma unroll
    for (int i = 0; i < NTHR / 32; i++) tot += s_tmp[i];
    float inv = 1.0f / (tot * (1.0f / C_H) + 1e-6f);
    __syncthreads();
    for (int k = tid; k < C_H; k += NTHR) {
        float nx = s_s[k] * inv;
        s_s[k] = 0.5f * (1.0f + __bfloat162float(grn_g[k]) * nx);
    }
    {
        float a0 = 0.f, a1 = 0.f, a2 = 0.f;
        int kbase = (tid >> 5) * (C_H / (NTHR / 32));
#pragma unroll 8
        for (int k = kbase; k < kbase + C_H / (NTHR / 32); k++) {
            float b = __bfloat162float(grn_b[k]);
            a0 = fmaf(b, __bfloat162float(w2[k * C_IN + lane]), a0);
            a1 = fmaf(b, __bfloat162float(w2[k * C_IN + lane + 32]), a1);
            a2 = fmaf(b, __bfloat162float(w2[k * C_IN + lane + 64]), a2);
        }
        atomicAdd(&s_c[lane], a0);
        atomicAdd(&s_c[lane + 32], a1);
        atomicAdd(&s_c[lane + 64], a2);
    }
    __syncthreads();
    for (int it = tid; it < 384 * 3; it += NTHR) {
        int kr = it & 7;
        int grp = (it >> 3) % 3;
        int kb = (it >> 3) / 3;
        int k = kb * 8 + kr;
        float sk = s_s[k];
        const uint4* src = reinterpret_cast<const uint4*>(w2 + k * C_IN + grp * 32);
        uint32_t wv[4][4];
#pragma unroll
        for (int qq = 0; qq < 4; qq++) {
            uint4 v = __ldg(src + qq);
            wv[qq][0] = v.x; wv[qq][1] = v.y; wv[qq][2] = v.z; wv[qq][3] = v.w;
        }
#pragma unroll
        for (int jj = 0; jj < 4; jj++) {
            uint32_t o[4];
#pragma unroll
            for (int qq = 0; qq < 4; qq++) o[qq] = pack_bf16(sk * bf_lo(wv[qq][jj]), sk * bf_hi(wv[qq][jj]));
            *reinterpret_cast<uint4*>(s_w2 + (grp * 4 + jj) * W2_SBO + kb * W2_LBO + kr * 16) = make_uint4(o[0], o[1], o[2], o[3]);
        }
    }
    proxy_fence();
    __syncthreads();

    unsigned char* ytile = s_y + wg * 12288;
    const uint32_t w1_base = smem_u32(s_w1);
    const uint32_t w2_base = smem_u32(s_w2);
    const uint32_t y_base = smem_u32(ytile);
    const int nwg = gridDim.x * NWG;
    for (int tile = blockIdx.x * NWG + wg; tile < NTILES; tile += nwg) {
#pragma unroll
        for (int it = 0; it < 2; it++) {
            int rl = warp * 16 + it * 8 + (lane >> 2);
            const uint4* p = reinterpret_cast<const uint4*>(x + ((size_t)tile * TILE_M + rl) * C_IN + q * 8);
            uint4 xv[3], y[3];
#pragma unroll
            for (int i = 0; i < 3; i++) xv[i] = __ldg(p + i * 4);
            ln_row4(xv, s_dw + 8 * q, y);
#pragma unroll
            for (int i = 0; i < 3; i++)
                *reinterpret_cast<uint4*>(ytile + (rl >> 3) * Y_SBO + (q + 4 * i) * Y_LBO + (rl & 7) * 16) = y[i];
        }
        proxy_fence();
        wg_bar(1 + wg);

        float O[48];
#pragma unroll
        for (int j = 0; j < 12; j++) {
            float2 cc = *reinterpret_cast<const float2*>(&s_c[32 * (j >> 2) + 8 * q + 2 * (j & 3)]);
            O[4 * j] = cc.x; O[4 * j + 1] = cc.y; O[4 * j + 2] = cc.x; O[4 * j + 3] = cc.y;
        }
        float S[32];
        uint32_t hf[16];
        wg_fence();
#pragma unroll
        for (int t = 0; t < 6; t++) {
            wgmma_ss_n64(S, make_desc(y_base + 2 * t * Y_LBO, Y_LBO, Y_SBO),
                         make_desc(w1_base + 2 * t * W1_LBO, W1_LBO, W1_SBO), t != 0);
        }
        wg_commit();
#pragma unroll
        for (int c = 0; c < 6; c++) {
            wg_wait<0>();
#pragma unroll
            for (int j = 0; j < 8; j++) {
                float g0 = gelu2(S[4 * j]);
                float g1 = gelu2(S[4 * j + 1]);
                float g2 = gelu2(S[4 * j + 2]);
                float g3 = gelu2(S[4 * j + 3]);
                hf[2 * j] = pack_bf16(g0, g1);
                hf[2 * j + 1] = pack_bf16(g2, g3);
            }
            wg_fence();
#pragma unroll
            for (int t = 0; t < 4; t++) {
                wgmma_n96(O, hf[4 * t], hf[4 * t + 1], hf[4 * t + 2], hf[4 * t + 3],
                          make_desc(w2_base + (c * 8 + 2 * t) * W2_LBO, W2_LBO, W2_SBO), 1);
            }
            if (c + 1 < 6) {
#pragma unroll
                for (int t = 0; t < 6; t++) {
                    wgmma_ss_n64(S, make_desc(y_base + 2 * t * Y_LBO, Y_LBO, Y_SBO),
                                 make_desc(w1_base + (c + 1) * 8 * W1_SBO + 2 * t * W1_LBO, W1_LBO, W1_SBO), t != 0);
                }
            }
            wg_commit();
        }
        wg_wait<0>();
        wg_bar(1 + wg);
        int r0 = tile * TILE_M + warp * 16 + (lane >> 2);
        const uint4* px0 = reinterpret_cast<const uint4*>(x + (size_t)r0 * C_IN + q * 8);
        const uint4* px1 = reinterpret_cast<const uint4*>(x + (size_t)(r0 + 8) * C_IN + q * 8);
        uint4* p0 = reinterpret_cast<uint4*>(out + (size_t)r0 * C_IN + q * 8);
        uint4* p1 = reinterpret_cast<uint4*>(out + (size_t)(r0 + 8) * C_IN + q * 8);
#pragma unroll
        for (int i = 0; i < 3; i++) {
            uint4 xa = __ldg(px0 + i * 4), xb = __ldg(px1 + i * 4);
            uint32_t wa[4] = {xa.x, xa.y, xa.z, xa.w};
            uint32_t wb[4] = {xb.x, xb.y, xb.z, xb.w};
            uint32_t oa[4], ob[4];
#pragma unroll
            for (int p = 0; p < 4; p++) {
                int j = i * 4 + p;
                oa[p] = pack_bf16(bf_lo(wa[p]) + O[4 * j], bf_hi(wa[p]) + O[4 * j + 1]);
                ob[p] = pack_bf16(bf_lo(wb[p]) + O[4 * j + 2], bf_hi(wb[p]) + O[4 * j + 3]);
            }
            p0[i * 4] = make_uint4(oa[0], oa[1], oa[2], oa[3]);
            p1[i * 4] = make_uint4(ob[0], ob[1], ob[2], ob[3]);
        }
    }
}

extern "C" void kernel_launch(void* const* d_in, const int* in_sizes, int n_in, void* d_out, int out_size) {
    const __nv_bfloat16* x = (const __nv_bfloat16*)d_in[0];
    const __nv_bfloat16* dw = (const __nv_bfloat16*)d_in[1];
    const __nv_bfloat16* w1 = (const __nv_bfloat16*)d_in[2];
    const __nv_bfloat16* w2 = (const __nv_bfloat16*)d_in[3];
    const __nv_bfloat16* grn_g = (const __nv_bfloat16*)d_in[4];
    const __nv_bfloat16* grn_b = (const __nv_bfloat16*)d_in[5];
    __nv_bfloat16* out = (__nv_bfloat16*)d_out;

    static int n_sm = 0;
    const int smem1 = 73728 + NWG * 24576 + 512 + 1536;
    const int smem2 = 2 * 73728 + NWG * 12288 + 512 + 512 + 1536 + 128;
    if (n_sm == 0) {
        int dev = 0;
        cudaGetDevice(&dev);
        cudaDeviceGetAttribute(&n_sm, cudaDevAttrMultiProcessorCount, dev);
        if (n_sm > MAX_CTAS) n_sm = MAX_CTAS;
        cudaFuncSetAttribute(k_stats, cudaFuncAttributeMaxDynamicSharedMemorySize, smem1);
        cudaFuncSetAttribute(k_main, cudaFuncAttributeMaxDynamicSharedMemorySize, smem2);
    }
    k_stats<<<n_sm, NTHR, smem1>>>(x, dw, w1);
    k_main<<<n_sm, NTHR, smem2>>>(x, dw, w1, w2, grn_g, grn_b, out, n_sm);
}
```

```cpp
#include <cuda_runtime.h>
#include <cuda_bf16.h>
#include <stdint.h>

#define C_IN 96
#define C_H 384
#define NROWS (512 * 512)
#define TILE_M 64
#define NTILES (NROWS / TILE_M)
#define MAX_CTAS 256

__device__ float g_partial[MAX_CTAS * C_H];

__device__ __forceinline__ uint32_t smem_u32(const void* p) {
    return (uint32_t)__cvta_generic_to_shared(p);
}
__device__ __forceinline__ uint64_t make_desc(uint32_t addr, uint32_t lbo, uint32_t sbo) {
    uint64_t d = 0;
    d |= (uint64_t)((addr & 0x3FFFF) >> 4);
    d |= (uint64_t)((lbo >> 4) & 0x3FFF) << 16;
    d |= (uint64_t)((sbo >> 4) & 0x3FFF) << 32;
    return d;
}
__device__ __forceinline__ void wg_fence() { asm volatile("wgmma.fence.sync.aligned;\n" ::: "memory"); }
__device__ __forceinline__ void wg_commit() { asm volatile("wgmma.commit_group.sync.aligned;\n" ::: "memory"); }
template <int N>
__device__ __forceinline__ void wg_wait() { asm volatile("wgmma.wait_group.sync.aligned %0;\n" ::"n"(N) : "memory"); }

__device__ __forceinline__ float tanh_approx(float x) {
    float y;
    asm("tanh.approx.f32 %0, %1;" : "=f"(y) : "f"(x));
    return y;
}
__device__ __forceinline__ uint32_t pack_bf16(float lo, float hi) {
    uint32_t r;
    asm("cvt.rn.bf16x2.f32 %0, %1, %2;" : "=r"(r) : "f"(hi), "f"(lo));
    return r;
}
__device__ __forceinline__ float bf_lo(uint32_t v) { return __uint_as_float(v << 16); }
__device__ __forceinline__ float bf_hi(uint32_t v) { return __uint_as_float(v & 0xffff0000u); }

__device__ __forceinline__ void wgmma_n64(float (&d)[32], uint32_t a0, uint32_t a1, uint32_t a2, uint32_t a3,
                                          uint64_t bdesc, int scale_d) {
    asm volatile(
        "{\n"
        ".reg .pred p;\n"
        "setp.ne.b32 p, %37, 0;\n"
        "wgmma.mma_async.sync.aligned.m64n64k16.f32.bf16.bf16 "
        "{%0, %1, %2, %3, %4, %5, %6, %7, %8, %9, %10, %11, %12, %13, %14, %15, "
        " %16, %17, %18, %19, %20, %21, %22, %23, %24, %25, %26, %27, %28, %29, %30, %31}, "
        "{%32, %33, %34, %35}, %36, p, 1, 1, 1;\n"
        "}\n"
        : "+f"(d[0]), "+f"(d[1]), "+f"(d[2]), "+f"(d[3]), "+f"(d[4]), "+f"(d[5]), "+f"(d[6]), "+f"(d[7]),
          "+f"(d[8]), "+f"(d[9]), "+f"(d[10]), "+f"(d[11]), "+f"(d[12]), "+f"(d[13]), "+f"(d[14]), "+f"(d[15]),
          "+f"(d[16]), "+f"(d[17]), "+f"(d[18]), "+f"(d[19]), "+f"(d[20]), "+f"(d[21]), "+f"(d[22]), "+f"(d[23]),
          "+f"(d[24]), "+f"(d[25]), "+f"(d[26]), "+f"(d[27]), "+f"(d[28]), "+f"(d[29]), "+f"(d[30]), "+f"(d[31])
        : "r"(a0), "r"(a1), "r"(a2), "r"(a3), "l"(bdesc), "r"(scale_d));
}

__device__ __forceinline__ void wgmma_n96(float (&d)[48], uint32_t a0, uint32_t a1, uint32_t a2, uint32_t a3,
                                          uint64_t bdesc, int scale_d) {
    asm volatile(
        "{\n"
        ".reg .pred p;\n"
        "setp.ne.b32 p, %53, 0;\n"
        "wgmma.mma_async.sync.aligned.m64n96k16.f32.bf16.bf16 "
        "{%0, %1, %2, %3, %4, %5, %6, %7, %8, %9, %10, %11, %12, %13, %14, %15, "
        " %16, %17, %18, %19, %20, %21, %22, %23, %24, %25, %26, %27, %28, %29, %30, %31, "
        " %32, %33, %34, %35, %36, %37, %38, %39, %40, %41, %42, %43, %44, %45, %46, %47}, "
        "{%48, %49, %50, %51}, %52, p, 1, 1, 1;\n"
        "}\n"
        : "+f"(d[0]), "+f"(d[1]), "+f"(d[2]), "+f"(d[3]), "+f"(d[4]), "+f"(d[5]), "+f"(d[6]), "+f"(d[7]),
          "+f"(d[8]), "+f"(d[9]), "+f"(d[10]), "+f"(d[11]), "+f"(d[12]), "+f"(d[13]), "+f"(d[14]), "+f"(d[15]),
          "+f"(d[16]), "+f"(d[17]), "+f"(d[18]), "+f"(d[19]), "+f"(d[20]), "+f"(d[21]), "+f"(d[22]), "+f"(d[23]),
          "+f"(d[24]), "+f"(d[25]), "+f"(d[26]), "+f"(d[27]), "+f"(d[28]), "+f"(d[29]), "+f"(d[30]), "+f"(d[31]),
          "+f"(d[32]), "+f"(d[33]), "+f"(d[34]), "+f"(d[35]), "+f"(d[36]), "+f"(d[37]), "+f"(d[38]), "+f"(d[39]),
          "+f"(d[40]), "+f"(d[41]), "+f"(d[42]), "+f"(d[43]), "+f"(d[44]), "+f"(d[45]), "+f"(d[46]), "+f"(d[47])
        : "r"(a0), "r"(a1), "r"(a2), "r"(a3), "l"(bdesc), "r"(scale_d));
}

__device__ __forceinline__ int k1_to_channel(int k) {
    int t = k >> 4, r = k & 15;
    int q = (r & 7) >> 1;
    int e = (r & 1) + ((r >> 3) << 1);
    return 32 * (t >> 1) + 8 * q + 4 * (t & 1) + e;
}
__device__ __forceinline__ int n2_to_channel(int n) {
    int j = n >> 3, r = n & 7;
    int q = r >> 1, e = r & 1;
    return 32 * (j >> 2) + 8 * q + 2 * (j & 3) + e;
}

#define W1_LBO 128
#define W1_SBO (12 * 128)
#define W2_LBO 128
#define W2_SBO (48 * 128)

__device__ __forceinline__ void stage_w1(unsigned char* sm, const __nv_bfloat16* __restrict__ w1, int tid, int nthreads) {
    for (int it = tid; it < 96 * 48; it += nthreads) {
        int kr = it & 7;
        int nb = (it >> 3) % 48;
        int kb = (it >> 3) / 48;
        int ch = k1_to_channel(kb * 8 + kr);
        uint4 v = __ldg(reinterpret_cast<const uint4*>(w1 + ch * C_H + nb * 8));
        *reinterpret_cast<uint4*>(sm + nb * W1_SBO + kb * W1_LBO + kr * 16) = v;
    }
}

struct XRows {
    uint4 a[3];
    uint4 b[3];
};

__device__ __forceinline__ void load_x(XRows& xr, const __nv_bfloat16* __restrict__ x, int tile, int warp, int lane) {
    int r0 = tile * TILE_M + warp * 16 + (lane >> 2);
    const uint4* p0 = reinterpret_cast<const uint4*>(x + (size_t)r0 * C_IN + (lane & 3) * 8);
    const uint4* p1 = reinterpret_cast<const uint4*>(x + (size_t)(r0 + 8) * C_IN + (lane & 3) * 8);
#pragma unroll
    for (int i = 0; i < 3; i++) {
        xr.a[i] = __ldg(p0 + i * 4);
        xr.b[i] = __ldg(p1 + i * 4);
    }
}

__device__ __forceinline__ void ln_row(const uint4 (&xv)[3], const float* __restrict__ dwv, uint32_t (&y)[12]) {
    float d[24];
    float s = 0.f;
#pragma unroll
    for (int i = 0; i < 3; i++) {
        uint32_t w[4] = {xv[i].x, xv[i].y, xv[i].z, xv[i].w};
#pragma unroll
        for (int p = 0; p < 4; p++) {
            d[i * 8 + 2 * p] = bf_lo(w[p]) * dwv[i * 8 + 2 * p];
            d[i * 8 + 2 * p + 1] = bf_hi(w[p]) * dwv[i * 8 + 2 * p + 1];
            s += d[i * 8 + 2 * p] + d[i * 8 + 2 * p + 1];
        }
    }
    s += __shfl_xor_sync(0xffffffffu, s, 1);
    s += __shfl_xor_sync(0xffffffffu, s, 2);
    float mean = s * (1.0f / C_IN);
    float v = 0.f;
#pragma unroll
    for (int i = 0; i < 24; i++) {
        d[i] -= mean;
        v = fmaf(d[i], d[i], v);
    }
    v += __shfl_xor_sync(0xffffffffu, v, 1);
    v += __shfl_xor_sync(0xffffffffu, v, 2);
    float rstd = rsqrtf(v * (1.0f / C_IN) + 1e-5f);
#pragma unroll
    for (int i = 0; i < 12; i++) y[i] = pack_bf16(d[2 * i] * rstd, d[2 * i + 1] * rstd);
}

#define GELU_C0 0.7978845608028654f
#define GELU_C1 (0.7978845608028654f * 0.044715f)

__device__ __forceinline__ float gelu2(float u) {
    float t = u * u;
    float p = fmaf(t, GELU_C1, GELU_C0);
    float a = p * u;
    float th = tanh_approx(a);
    return fmaf(u, th, u);
}


__device__ __forceinline__ void wgmma_ss_n128_tA(float (&d)[64], uint64_t adesc, uint64_t bdesc, int scale_d) {
    asm volatile(
        "{\n"
        ".reg .pred p;\n"
        "setp.ne.b32 p, %66, 0;\n"
        "wgmma.mma_async.sync.aligned.m64n128k16.f32.bf16.bf16 "
        "{%0, %1, %2, %3, %4, %5, %6, %7, %8, %9, %10, %11, %12, %13, %14, %15, "
        " %16, %17, %18, %19, %20, %21, %22, %23, %24, %25, %26, %27, %28, %29, %30, %31, "
        " %32, %33, %34, %35, %36, %37, %38, %39, %40, %41, %42, %43, %44, %45, %46, %47, "
        " %48, %49, %50, %51, %52, %53, %54, %55, %56, %57, %58, %59, %60, %61, %62, %63}, "
        "%64, %65, p, 1, 1, 1, 0;\n"
        "}\n"
        : "+f"(d[0]), "+f"(d[1]), "+f"(d[2]), "+f"(d[3]), "+f"(d[4]), "+f"(d[5]), "+f"(d[6]), "+f"(d[7]),
          "+f"(d[8]), "+f"(d[9]), "+f"(d[10]), "+f"(d[11]), "+f"(d[12]), "+f"(d[13]), "+f"(d[14]), "+f"(d[15]),
          "+f"(d[16]), "+f"(d[17]), "+f"(d[18]), "+f"(d[19]), "+f"(d[20]), "+f"(d[21]), "+f"(d[22]), "+f"(d[23]),
          "+f"(d[24]), "+f"(d[25]), "+f"(d[26]), "+f"(d[27]), "+f"(d[28]), "+f"(d[29]), "+f"(d[30]), "+f"(d[31]),
          "+f"(d[32]), "+f"(d[33]), "+f"(d[34]), "+f"(d[35]), "+f"(d[36]), "+f"(d[37]), "+f"(d[38]), "+f"(d[39]),
          "+f"(d[40]), "+f"(d[41]), "+f"(d[42]), "+f"(d[43]), "+f"(d[44]), "+f"(d[45]), "+f"(d[46]), "+f"(d[47]),
          "+f"(d[48]), "+f"(d[49]), "+f"(d[50]), "+f"(d[51]), "+f"(d[52]), "+f"(d[53]), "+f"(d[54]), "+f"(d[55]),
          "+f"(d[56]), "+f"(d[57]), "+f"(d[58]), "+f"(d[59]), "+f"(d[60]), "+f"(d[61]), "+f"(d[62]), "+f"(d[63])
        : "l"(adesc), "l"(bdesc), "r"(scale_d));
}
__device__ __forceinline__ void wgmma_ss_n64(float (&d)[32], uint64_t adesc, uint64_t bdesc, int scale_d) {
    asm volatile(
        "{\n"
        ".reg .pred p;\n"
        "setp.ne.b32 p, %34, 0;\n"
        "wgmma.mma_async.sync.aligned.m64n64k16.f32.bf16.bf16 "
        "{%0, %1, %2, %3, %4, %5, %6, %7, %8, %9, %10, %11, %12, %13, %14, %15, "
        " %16, %17, %18, %19, %20, %21, %22, %23, %24, %25, %26, %27, %28, %29, %30, %31}, "
        "%32, %33, p, 1, 1, 0, 1;\n"
        "}\n"
        : "+f"(d[0]), "+f"(d[1]), "+f"(d[2]), "+f"(d[3]), "+f"(d[4]), "+f"(d[5]), "+f"(d[6]), "+f"(d[7]),
          "+f"(d[8]), "+f"(d[9]), "+f"(d[10]), "+f"(d[11]), "+f"(d[12]), "+f"(d[13]), "+f"(d[14]), "+f"(d[15]),
          "+f"(d[16]), "+f"(d[17]), "+f"(d[18]), "+f"(d[19]), "+f"(d[20]), "+f"(d[21]), "+f"(d[22]), "+f"(d[23]),
          "+f"(d[24]), "+f"(d[25]), "+f"(d[26]), "+f"(d[27]), "+f"(d[28]), "+f"(d[29]), "+f"(d[30]), "+f"(d[31])
        : "l"(adesc), "l"(bdesc), "r"(scale_d));
}
__device__ __forceinline__ void wg_bar(int id) { asm volatile("bar.sync %0, 128;" ::"r"(id) : "memory"); }
__device__ __forceinline__ void proxy_fence() { asm volatile("fence.proxy.async.shared::cta;\n" ::: "memory"); }

__device__ __forceinline__ void ln_row4(const uint4 (&xv)[3], const float* __restrict__ s_dwq, uint4 (&y)[3]) {
    float d[24];
    float s = 0.f;
#pragma unroll
    for (int i = 0; i < 3; i++) {
        uint32_t w[4] = {xv[i].x, xv[i].y, xv[i].z, xv[i].w};
        float4 da = *reinterpret_cast<const float4*>(s_dwq + 32 * i);
        float4 db = *reinterpret_cast<const float4*>(s_dwq + 32 * i + 4);
        d[i * 8 + 0] = bf_lo(w[0]) * da.x; d[i * 8 + 1] = bf_hi(w[0]) * da.y;
        d[i * 8 + 2] = bf_lo(w[1]) * da.z; d[i * 8 + 3] = bf_hi(w[1]) * da.w;
        d[i * 8 + 4] = bf_lo(w[2]) * db.x; d[i * 8 + 5] = bf_hi(w[2]) * db.y;
        d[i * 8 + 6] = bf_lo(w[3]) * db.z; d[i * 8 + 7] = bf_hi(w[3]) * db.w;
#pragma unroll
        for (int p = 0; p < 8; p++) s += d[i * 8 + p];
    }
    s += __shfl_xor_sync(0xffffffffu, s, 1);
    s += __shfl_xor_sync(0xffffffffu, s, 2);
    float mean = s * (1.0f / C_IN);
    float v = 0.f;
#pragma unroll
    for (int i = 0; i < 24; i++) {
        d[i] -= mean;
        v = fmaf(d[i], d[i], v);
    }
    v += __shfl_xor_sync(0xffffffffu, v, 1);
    v += __shfl_xor_sync(0xffffffffu, v, 2);
    float rstd = rsqrtf(v * (1.0f / C_IN) + 1e-5f);
#pragma unroll
    for (int i = 0; i < 3; i++) {
        y[i].x = pack_bf16(d[i * 8 + 0] * rstd, d[i * 8 + 1] * rstd);
        y[i].y = pack_bf16(d[i * 8 + 2] * rstd, d[i * 8 + 3] * rstd);
        y[i].z = pack_bf16(d[i * 8 + 4] * rstd, d[i * 8 + 5] * rstd);
        y[i].w = pack_bf16(d[i * 8 + 6] * rstd, d[i * 8 + 7] * rstd);
    }
}

__device__ __forceinline__ void stage_w1n(unsigned char* sm, const __nv_bfloat16* __restrict__ w1, int tid, int nthreads) {
    for (int it = tid; it < 96 * 48; it += nthreads) {
        int kr = it & 7;
        int nb = (it >> 3) % 48;
        int kb = (it >> 3) / 48;
        int ch = kb * 8 + kr;
        uint4 v = __ldg(reinterpret_cast<const uint4*>(w1 + ch * C_H + nb * 8));
        *reinterpret_cast<uint4*>(sm + nb * W1_SBO + kb * W1_LBO + kr * 16) = v;
    }
}

#define Y_LBO 128
#define Y_SBO (12 * 128)

#define NWG 4
#define NTHR (NWG * 128)
#define P1_ROWS 128
#define P1_TILES (NROWS / P1_ROWS)

__device__ __forceinline__ void wgmma_ss_n64_tA(float (&d)[32], uint64_t adesc, uint64_t bdesc, int scale_d) {
    asm volatile(
        "{\n"
        ".reg .pred p;\n"
        "setp.ne.b32 p, %34, 0;\n"
        "wgmma.mma_async.sync.aligned.m64n64k16.f32.bf16.bf16 "
        "{%0, %1, %2, %3, %4, %5, %6, %7, %8, %9, %10, %11, %12, %13, %14, %15, "
        " %16, %17, %18, %19, %20, %21, %22, %23, %24, %25, %26, %27, %28, %29, %30, %31}, "
        "%32, %33, p, 1, 1, 1, 0;\n"
        "}\n"
        : "+f"(d[0]), "+f"(d[1]), "+f"(d[2]), "+f"(d[3]), "+f"(d[4]), "+f"(d[5]), "+f"(d[6]), "+f"(d[7]),
          "+f"(d[8]), "+f"(d[9]), "+f"(d[10]), "+f"(d[11]), "+f"(d[12]), "+f"(d[13]), "+f"(d[14]), "+f"(d[15]),
          "+f"(d[16]), "+f"(d[17]), "+f"(d[18]), "+f"(d[19]), "+f"(d[20]), "+f"(d[21]), "+f"(d[22]), "+f"(d[23]),
          "+f"(d[24]), "+f"(d[25]), "+f"(d[26]), "+f"(d[27]), "+f"(d[28]), "+f"(d[29]), "+f"(d[30]), "+f"(d[31])
        : "l"(adesc), "l"(bdesc), "r"(scale_d));
}

__global__ void __launch_bounds__(NTHR, 1)
k_stats(const __nv_bfloat16* __restrict__ x, const __nv_bfloat16* __restrict__ dw, const __nv_bfloat16* __restrict__ w1) {
    extern __shared__ __align__(1024) unsigned char smem[];
    unsigned char* s_w1 = smem;
    unsigned char* s_y = smem + 73728;
    float* s_dw = reinterpret_cast<float*>(smem + 73728 + NWG * 12288);
    float* s_red = s_dw + 128;

    const int tid = threadIdx.x;
    const int wg = tid >> 7;
    const int warp = (tid >> 5) & 3;
    const int lane = tid & 31;
    const int q = lane & 3;

    const int nwg = gridDim.x * NWG;
    int tile = blockIdx.x * NWG + wg;
    XRows xn;
    if (tile < NTILES) load_x(xn, x, tile, warp, lane);

    stage_w1n(s_w1, w1, tid, NTHR);
    if (tid < C_IN) s_dw[tid] = __bfloat162float(dw[tid]);
    for (int i = tid; i < C_H; i += NTHR) s_red[i] = 0.f;
    proxy_fence();
    __syncthreads();

    float ss[12];
#pragma unroll
    for (int i = 0; i < 12; i++) ss[i] = 0.f;

    unsigned char* ytile = s_y + wg * 12288;
    const uint32_t w1_base = smem_u32(s_w1);
    const uint32_t y_base = smem_u32(ytile);
    const int rl = warp * 16 + (lane >> 2);
    unsigned char* yp = ytile + (rl >> 3) * Y_SBO + q * Y_LBO + (rl & 7) * 16;
    for (; tile < NTILES; tile += nwg) {
        {
            uint4 y[3];
            ln_row4(xn.a, s_dw + 8 * q, y);
#pragma unroll
            for (int i = 0; i < 3; i++) *reinterpret_cast<uint4*>(yp + 4 * i * Y_LBO) = y[i];
            ln_row4(xn.b, s_dw + 8 * q, y);
#pragma unroll
            for (int i = 0; i < 3; i++) *reinterpret_cast<uint4*>(yp + Y_SBO + 4 * i * Y_LBO) = y[i];
        }
        proxy_fence();
        wg_bar(1 + wg);
        if (tile + nwg < NTILES) load_x(xn, x, tile + nwg, warp, lane);
        float S[2][32];
        wg_fence();
#pragma unroll
        for (int t = 0; t < 6; t++) {
            wgmma_ss_n64_tA(S[0], make_desc(w1_base + 2 * t * W1_LBO, W1_LBO, W1_SBO),
                            make_desc(y_base + 2 * t * Y_LBO, Y_LBO, Y_SBO), t != 0);
        }
        wg_commit();
#pragma unroll
        for (int m = 0; m < 6; m++) {
            if (m + 1 < 6) {
                wg_fence();
#pragma unroll
                for (int t = 0; t < 6; t++) {
                    wgmma_ss_n64_tA(S[(m + 1) & 1], make_desc(w1_base + (m + 1) * 8 * W1_SBO + 2 * t * W1_LBO, W1_LBO, W1_SBO),
                                    make_desc(y_base + 2 * t * Y_LBO, Y_LBO, Y_SBO), t != 0);
                }
                wg_commit();
                wg_wait<1>();
            } else {
                wg_wait<0>();
            }
            float(&Sc)[32] = S[m & 1];
            float a0 = ss[2 * m], a1 = ss[2 * m + 1];
#pragma unroll
            for (int j = 0; j < 8; j++) {
                float g0 = gelu2(Sc[4 * j]);
                float g1 = gelu2(Sc[4 * j + 1]);
                float g2 = gelu2(Sc[4 * j + 2]);
                float g3 = gelu2(Sc[4 * j + 3]);
                a0 = fmaf(g0, g0, a0);
                a1 = fmaf(g2, g2, a1);
                a0 = fmaf(g1, g1, a0);
                a1 = fmaf(g3, g3, a1);
            }
            ss[2 * m] = a0;
            ss[2 * m + 1] = a1;
        }
        wg_bar(1 + wg);
    }
#pragma unroll
    for (int i = 0; i < 12; i++) {
        float v = ss[i];
        v += __shfl_xor_sync(0xffffffffu, v, 1);
        v += __shfl_xor_sync(0xffffffffu, v, 2);
        if (q == 0) {
            int m = i >> 1, hh = i & 1;
            atomicAdd(&s_red[m * 64 + warp * 16 + hh * 8 + (lane >> 2)], v);
        }
    }
    __syncthreads();
    for (int i = tid; i < C_H; i += NTHR) g_partial[blockIdx.x * C_H + i] = s_red[i] * 0.25f;
}

__global__ void __launch_bounds__(NTHR, 1)
k_main(const __nv_bfloat16* __restrict__ x, const __nv_bfloat16* __restrict__ dw, const __nv_bfloat16* __restrict__ w1,
       const __nv_bfloat16* __restrict__ w2, const __nv_bfloat16* __restrict__ grn_g,
       const __nv_bfloat16* __restrict__ grn_b, __nv_bfloat16* __restrict__ out, int n_part) {
    extern __shared__ __align__(1024) unsigned char smem[];
    unsigned char* s_w1 = smem;
    unsigned char* s_w2 = smem + 73728;
    unsigned char* s_y = smem + 2 * 73728;
    float* s_dw = reinterpret_cast<float*>(smem + 2 * 73728 + NWG * 12288);
    float* s_c = s_dw + 128;
    float* s_s = s_c + 128;
    float* s_tmp = s_s + 384;

    const int tid = threadIdx.x;
    const int wg = tid >> 7;
    const int warp = (tid >> 5) & 3;
    const int lane = tid & 31;
    const int q = lane & 3;

    stage_w1n(s_w1, w1, tid, NTHR);
    if (tid < C_IN) { s_dw[tid] = __bfloat162float(dw[tid]); s_c[tid] = 0.f; }
    float lsum = 0.f;
    for (int k = tid; k < C_H; k += NTHR) {
        float a = 0.f;
        for (int b = 0; b < n_part; b++) a += g_partial[b * C_H + k];
        float gx = sqrtf(a + 1e-6f);
        s_s[k] = gx;
        lsum += gx;
    }
#pragma unroll
    for (int o = 16; o > 0; o >>= 1) lsum += __shfl_xor_sync(0xffffffffu, lsum, o);
    if (lane == 0) s_tmp[tid >> 5] = lsum;
    __syncthreads();
    float tot = 0.f;
#pragma unroll
    for (int i = 0; i < NTHR / 32; i++) tot += s_tmp[i];
    float inv = 1.0f / (tot * (1.0f / C_H) + 1e-6f);
    __syncthreads();
    for (int k = tid; k < C_H; k += NTHR) {
        float nx = s_s[k] * inv;
        s_s[k] = 0.5f * (1.0f + __bfloat162float(grn_g[k]) * nx);
    }
    {
        float a0 = 0.f, a1 = 0.f, a2 = 0.f;
        int kbase = (tid >> 5) * (C_H / (NTHR / 32));
#pragma unroll 8
        for (int k = kbase; k < kbase + C_H / (NTHR / 32); k++) {
            float b = __bfloat162float(grn_b[k]);
            a0 = fmaf(b, __bfloat162float(w2[k * C_IN + lane]), a0);
            a1 = fmaf(b, __bfloat162float(w2[k * C_IN + lane + 32]), a1);
            a2 = fmaf(b, __bfloat162float(w2[k * C_IN + lane + 64]), a2);
        }
        atomicAdd(&s_c[lane], a0);
        atomicAdd(&s_c[lane + 32], a1);
        atomicAdd(&s_c[lane + 64], a2);
    }
    __syncthreads();
    for (int it = tid; it < 384 * 3; it += NTHR) {
        int kr = it & 7;
        int grp = (it >> 3) % 3;
        int kb = (it >> 3) / 3;
        int k = kb * 8 + kr;
        float sk = s_s[k];
        const uint4* src = reinterpret_cast<const uint4*>(w2 + k * C_IN + grp * 32);
        uint32_t wv[4][4];
#pragma unroll
        for (int qq = 0; qq < 4; qq++) {
            uint4 v = __ldg(src + qq);
            wv[qq][0] = v.x; wv[qq][1] = v.y; wv[qq][2] = v.z; wv[qq][3] = v.w;
        }
#pragma unroll
        for (int jj = 0; jj < 4; jj++) {
            uint32_t o[4];
#pragma unroll
            for (int qq = 0; qq < 4; qq++) o[qq] = pack_bf16(sk * bf_lo(wv[qq][jj]), sk * bf_hi(wv[qq][jj]));
            *reinterpret_cast<uint4*>(s_w2 + (grp * 4 + jj) * W2_SBO + kb * W2_LBO + kr * 16) = make_uint4(o[0], o[1], o[2], o[3]);
        }
    }
    proxy_fence();
    __syncthreads();

    unsigned char* ytile = s_y + wg * 12288;
    const uint32_t w1_base = smem_u32(s_w1);
    const uint32_t w2_base = smem_u32(s_w2);
    const uint32_t y_base = smem_u32(ytile);
    const int nwg = gridDim.x * NWG;
    for (int tile = blockIdx.x * NWG + wg; tile < NTILES; tile += nwg) {
#pragma unroll
        for (int it = 0; it < 2; it++) {
            int rl = warp * 16 + it * 8 + (lane >> 2);
            const uint4* p = reinterpret_cast<const uint4*>(x + ((size_t)tile * TILE_M + rl) * C_IN + q * 8);
            uint4 xv[3], y[3];
#pragma unroll
            for (int i = 0; i < 3; i++) xv[i] = __ldg(p + i * 4);
            ln_row4(xv, s_dw + 8 * q, y);
#pragma unroll
            for (int i = 0; i < 3; i++)
                *reinterpret_cast<uint4*>(ytile + (rl >> 3) * Y_SBO + (q + 4 * i) * Y_LBO + (rl & 7) * 16) = y[i];
        }
        proxy_fence();
        wg_bar(1 + wg);

        float O[48];
#pragma unroll
        for (int j = 0; j < 12; j++) {
            float2 cc = *reinterpret_cast<const float2*>(&s_c[32 * (j >> 2) + 8 * q + 2 * (j & 3)]);
            O[4 * j] = cc.x; O[4 * j + 1] = cc.y; O[4 * j + 2] = cc.x; O[4 * j + 3] = cc.y;
        }
        float S[32];
        uint32_t hf[16];
        wg_fence();
#pragma unroll
        for (int t = 0; t < 6; t++) {
            wgmma_ss_n64(S, make_desc(y_base + 2 * t * Y_LBO, Y_LBO, Y_SBO),
                         make_desc(w1_base + 2 * t * W1_LBO, W1_LBO, W1_SBO), t != 0);
        }
        wg_commit();
#pragma unroll
        for (int c = 0; c < 6; c++) {
            wg_wait<0>();
#pragma unroll
            for (int j = 0; j < 8; j++) {
                float g0 = gelu2(S[4 * j]);
                float g1 = gelu2(S[4 * j + 1]);
                float g2 = gelu2(S[4 * j + 2]);
                float g3 = gelu2(S[4 * j + 3]);
                hf[2 * j] = pack_bf16(g0, g1);
                hf[2 * j + 1] = pack_bf16(g2, g3);
            }
            wg_fence();
#pragma unroll
            for (int t = 0; t < 4; t++) {
                wgmma_n96(O, hf[4 * t], hf[4 * t + 1], hf[4 * t + 2], hf[4 * t + 3],
                          make_desc(w2_base + (c * 8 + 2 * t) * W2_LBO, W2_LBO, W2_SBO), 1);
            }
            if (c + 1 < 6) {
#pragma unroll
                for (int t = 0; t < 6; t++) {
                    wgmma_ss_n64(S, make_desc(y_base + 2 * t * Y_LBO, Y_LBO, Y_SBO),
                                 make_desc(w1_base + (c + 1) * 8 * W1_SBO + 2 * t * W1_LBO, W1_LBO, W1_SBO), t != 0);
                }
            }
            wg_commit();
        }
        wg_wait<0>();
        wg_bar(1 + wg);
        int r0 = tile * TILE_M + warp * 16 + (lane >> 2);
        const uint4* px0 = reinterpret_cast<const uint4*>(x + (size_t)r0 * C_IN + q * 8);
        const uint4* px1 = reinterpret_cast<const uint4*>(x + (size_t)(r0 + 8) * C_IN + q * 8);
        uint4* p0 = reinterpret_cast<uint4*>(out + (size_t)r0 * C_IN + q * 8);
        uint4* p1 = reinterpret_cast<uint4*>(out + (size_t)(r0 + 8) * C_IN + q * 8);
#pragma unroll
        for (int i = 0; i < 3; i++) {
            uint4 xa = __ldg(px0 + i * 4), xb = __ldg(px1 + i * 4);
            uint32_t wa[4] = {xa.x, xa.y, xa.z, xa.w};
            uint32_t wb[4] = {xb.x, xb.y, xb.z, xb.w};
            uint32_t oa[4], ob[4];
#pragma unroll
            for (int p = 0; p < 4; p++) {
                int j = i * 4 + p;
                oa[p] = pack_bf16(bf_lo(wa[p]) + O[4 * j], bf_hi(wa[p]) + O[4 * j + 1]);
                ob[p] = pack_bf16(bf_lo(wb[p]) + O[4 * j + 2], bf_hi(wb[p]) + O[4 * j + 3]);
            }
            p0[i * 4] = make_uint4(oa[0], oa[1], oa[2], oa[3]);
            p1[i * 4] = make_uint4(ob[0], ob[1], ob[2], ob[3]);
        }
    }
}

extern "C" void kernel_launch(void* const* d_in, const int* in_sizes, int n_in, void* d_out, int out_size) {
    const __nv_bfloat16* x = (const __nv_bfloat16*)d_in[0];
    const __nv_bfloat16* dw = (const __nv_bfloat16*)d_in[1];
    const __nv_bfloat16* w1 = (const __nv_bfloat16*)d_in[2];
    const __nv_bfloat16* w2 = (const __nv_bfloat16*)d_in[3];
    const __nv_bfloat16* grn_g = (const __nv_bfloat16*)d_in[4];
    const __nv_bfloat16* grn_b = (const __nv_bfloat16*)d_in[5];
    __nv_bfloat16* out = (__nv_bfloat16*)d_out;

    static int n_sm = 0;
    const int smem1 = 73728 + NWG * 12288 + 512 + 1536;
    const int smem2 = 2 * 73728 + NWG * 12288 + 512 + 512 + 1536 + 128;
    if (n_sm == 0) {
        int dev = 0;
        cudaGetDevice(&dev);
        cudaDeviceGetAttribute(&n_sm, cudaDevAttrMultiProcessorCount, dev);
        if (n_sm > MAX_CTAS) n_sm = MAX_CTAS;
        cudaFuncSetAttribute(k_stats, cudaFuncAttributeMaxDynamicSharedMemorySize, smem1);
        cudaFuncSetAttribute(k_main, cudaFuncAttributeMaxDynamicSharedMemorySize, smem2);
    }
    k_stats<<<n_sm, NTHR, smem1>>>(x, dw, w1);
    k_main<<<n_sm, NTHR, smem2>>>(x, dw, w1, w2, grn_g, grn_b, out, n_sm);
}
```

```cpp
#include <cuda_runtime.h>
#include <cuda_bf16.h>
#include <stdint.h>

#define C_IN 96
#define C_H 384
#define NROWS (512 * 512)
#define TILE_M 64
#define NTILES (NROWS / TILE_M)
#define MAX_CTAS 256
#define NWG 4
#define NTHR (NWG * 128)

__device__ float g_partial[MAX_CTAS * C_H];

#define GELU_KAPPA 0.3292034911525734f
#define GELU_C0K 2.423681954311584f

__device__ __forceinline__ uint32_t smem_u32(const void* p) { return (uint32_t)__cvta_generic_to_shared(p); }
__device__ __forceinline__ uint64_t make_desc(uint32_t addr, uint32_t lbo, uint32_t sbo) {
    uint64_t d = 0;
    d |= (uint64_t)((addr & 0x3FFFF) >> 4);
    d |= (uint64_t)((lbo >> 4) & 0x3FFF) << 16;
    d |= (uint64_t)((sbo >> 4) & 0x3FFF) << 32;
    return d;
}
__device__ __forceinline__ void wg_fence() { asm volatile("wgmma.fence.sync.aligned;\n" ::: "memory"); }
__device__ __forceinline__ void wg_commit() { asm volatile("wgmma.commit_group.sync.aligned;\n" ::: "memory"); }
template <int N>
__device__ __forceinline__ void wg_wait() { asm volatile("wgmma.wait_group.sync.aligned %0;\n" ::"n"(N) : "memory"); }
__device__ __forceinline__ void wg_bar(int id) { asm volatile("bar.sync %0, 128;" ::"r"(id) : "memory"); }
__device__ __forceinline__ void proxy_fence() { asm volatile("fence.proxy.async.shared::cta;\n" ::: "memory"); }
__device__ __forceinline__ void cp_async16(uint32_t dst, const void* src) {
    asm volatile("cp.async.cg.shared.global [%0], [%1], 16;\n" ::"r"(dst), "l"(src) : "memory");
}
__device__ __forceinline__ void cp_async_commit() { asm volatile("cp.async.commit_group;\n" ::: "memory"); }
__device__ __forceinline__ void cp_async_wait_all() { asm volatile("cp.async.wait_group 0;\n" ::: "memory"); }
__device__ __forceinline__ void prefetch_l2(const void* p) { asm volatile("prefetch.global.L2 [%0];\n" ::"l"(p)); }

__device__ __forceinline__ float tanh_approx(float x) {
    float y;
    asm("tanh.approx.f32 %0, %1;" : "=f"(y) : "f"(x));
    return y;
}
__device__ __forceinline__ uint32_t pack_bf16(float lo, float hi) {
    uint32_t r;
    asm("cvt.rn.bf16x2.f32 %0, %1, %2;" : "=r"(r) : "f"(hi), "f"(lo));
    return r;
}
__device__ __forceinline__ float bf_lo(uint32_t v) { return __uint_as_float(v << 16); }
__device__ __forceinline__ float bf_hi(uint32_t v) { return __uint_as_float(v & 0xffff0000u); }

#define ACC32(d)                                                                                             \
    "+f"(d[0]), "+f"(d[1]), "+f"(d[2]), "+f"(d[3]), "+f"(d[4]), "+f"(d[5]), "+f"(d[6]), "+f"(d[7]),          \
        "+f"(d[8]), "+f"(d[9]), "+f"(d[10]), "+f"(d[11]), "+f"(d[12]), "+f"(d[13]), "+f"(d[14]), "+f"(d[15]), \
        "+f"(d[16]), "+f"(d[17]), "+f"(d[18]), "+f"(d[19]), "+f"(d[20]), "+f"(d[21]), "+f"(d[22]),           \
        "+f"(d[23]), "+f"(d[24]), "+f"(d[25]), "+f"(d[26]), "+f"(d[27]), "+f"(d[28]), "+f"(d[29]),           \
        "+f"(d[30]), "+f"(d[31])
#define ACC32_STR                                                                \
    "{%0, %1, %2, %3, %4, %5, %6, %7, %8, %9, %10, %11, %12, %13, %14, %15, "    \
    " %16, %17, %18, %19, %20, %21, %22, %23, %24, %25, %26, %27, %28, %29, %30, %31}"

__device__ __forceinline__ void wgmma_ss_n64_tA(float (&d)[32], uint64_t adesc, uint64_t bdesc, int scale_d) {
    asm volatile(
        "{\n.reg .pred p;\nsetp.ne.b32 p, %34, 0;\n"
        "wgmma.mma_async.sync.aligned.m64n64k16.f32.bf16.bf16 " ACC32_STR ", %32, %33, p, 1, 1, 1, 0;\n}\n"
        : ACC32(d)
        : "l"(adesc), "l"(bdesc), "r"(scale_d));
}
__device__ __forceinline__ void wgmma_ss_n64(float (&d)[32], uint64_t adesc, uint64_t bdesc, int scale_d) {
    asm volatile(
        "{\n.reg .pred p;\nsetp.ne.b32 p, %34, 0;\n"
        "wgmma.mma_async.sync.aligned.m64n64k16.f32.bf16.bf16 " ACC32_STR ", %32, %33, p, 1, 1, 0, 1;\n}\n"
        : ACC32(d)
        : "l"(adesc), "l"(bdesc), "r"(scale_d));
}
__device__ __forceinline__ void wgmma_n96(float (&d)[48], uint32_t a0, uint32_t a1, uint32_t a2, uint32_t a3,
                                          uint64_t bdesc) {
    asm volatile(
        "{\n"
        "wgmma.mma_async.sync.aligned.m64n96k16.f32.bf16.bf16 "
        "{%0, %1, %2, %3, %4, %5, %6, %7, %8, %9, %10, %11, %12, %13, %14, %15, "
        " %16, %17, %18, %19, %20, %21, %22, %23, %24, %25, %26, %27, %28, %29, %30, %31, "
        " %32, %33, %34, %35, %36, %37, %38, %39, %40, %41, %42, %43, %44, %45, %46, %47}, "
        "{%48, %49, %50, %51}, %52, 1, 1, 1, 1;\n"
        "}\n"
        : ACC32(d), "+f"(d[32]), "+f"(d[33]), "+f"(d[34]), "+f"(d[35]), "+f"(d[36]), "+f"(d[37]), "+f"(d[38]),
          "+f"(d[39]), "+f"(d[40]), "+f"(d[41]), "+f"(d[42]), "+f"(d[43]), "+f"(d[44]), "+f"(d[45]), "+f"(d[46]),
          "+f"(d[47])
        : "r"(a0), "r"(a1), "r"(a2), "r"(a3), "l"(bdesc));
}

#define W1_LBO 128
#define W1_SBO (12 * 128)
#define W2_LBO 128
#define W2_SBO (48 * 128)
#define Y_LBO 128
#define Y_SBO (12 * 128)

__device__ __forceinline__ void stage_w1_async(uint32_t sm, const __nv_bfloat16* __restrict__ w1, int tid) {
#pragma unroll
    for (int i = 0; i < 96 * 48 / NTHR; i++) {
        int it = tid + i * NTHR;
        int kr = it & 7;
        int nb = (it >> 3) % 48;
        int kb = (it >> 3) / 48;
        cp_async16(sm + nb * W1_SBO + kb * W1_LBO + kr * 16, w1 + (kb * 8 + kr) * C_H + nb * 8);
    }
}

__device__ __forceinline__ void ln_row4(const uint4 (&xv)[3], const float* __restrict__ s_dwq, uint4 (&y)[3]) {
    float xf[24], dwf[24];
    float s = 0.f;
#pragma unroll
    for (int i = 0; i < 3; i++) {
        uint32_t w[4] = {xv[i].x, xv[i].y, xv[i].z, xv[i].w};
        float4 da = *reinterpret_cast<const float4*>(s_dwq + 32 * i);
        float4 db = *reinterpret_cast<const float4*>(s_dwq + 32 * i + 4);
        dwf[i * 8 + 0] = da.x; dwf[i * 8 + 1] = da.y; dwf[i * 8 + 2] = da.z; dwf[i * 8 + 3] = da.w;
        dwf[i * 8 + 4] = db.x; dwf[i * 8 + 5] = db.y; dwf[i * 8 + 6] = db.z; dwf[i * 8 + 7] = db.w;
#pragma unroll
        for (int p = 0; p < 4; p++) {
            xf[i * 8 + 2 * p] = bf_lo(w[p]);
            xf[i * 8 + 2 * p + 1] = bf_hi(w[p]);
        }
#pragma unroll
        for (int p = 0; p < 8; p++) s = fmaf(xf[i * 8 + p], dwf[i * 8 + p], s);
    }
    s += __shfl_xor_sync(0xffffffffu, s, 1);
    s += __shfl_xor_sync(0xffffffffu, s, 2);
    float nmean = s * (-1.0f / C_IN);
    float v = 0.f;
#pragma unroll
    for (int i = 0; i < 24; i++) {
        xf[i] = fmaf(xf[i], dwf[i], nmean);
        v = fmaf(xf[i], xf[i], v);
    }
    v += __shfl_xor_sync(0xffffffffu, v, 1);
    v += __shfl_xor_sync(0xffffffffu, v, 2);
    float rstd = rsqrtf(v * (1.0f / C_IN) + 1e-5f) * GELU_KAPPA;
#pragma unroll
    for (int i = 0; i < 3; i++) {
        y[i].x = pack_bf16(xf[i * 8 + 0] * rstd, xf[i * 8 + 1] * rstd);
        y[i].y = pack_bf16(xf[i * 8 + 2] * rstd, xf[i * 8 + 3] * rstd);
        y[i].z = pack_bf16(xf[i * 8 + 4] * rstd, xf[i * 8 + 5] * rstd);
        y[i].w = pack_bf16(xf[i * 8 + 6] * rstd, xf[i * 8 + 7] * rstd);
    }
}

__device__ __forceinline__ float gelu2(float u) {
    float t = fmaf(u, u, GELU_C0K);
    float a = t * u;
    float th = tanh_approx(a);
    return fmaf(u, th, u);
}

struct XRows {
    uint4 a[3];
    uint4 b[3];
};
__device__ __forceinline__ void load_x(XRows& xr, const __nv_bfloat16* __restrict__ x, int tile, int warp, int lane) {
    int r0 = tile * TILE_M + warp * 16 + (lane >> 2);
    const uint4* p0 = reinterpret_cast<const uint4*>(x + (size_t)r0 * C_IN + (lane & 3) * 8);
    const uint4* p1 = reinterpret_cast<const uint4*>(x + (size_t)(r0 + 8) * C_IN + (lane & 3) * 8);
#pragma unroll
    for (int i = 0; i < 3; i++) {
        xr.a[i] = __ldg(p0 + i * 4);
        xr.b[i] = __ldg(p1 + i * 4);
    }
}

__global__ void __launch_bounds__(NTHR, 1)
k_stats(const __nv_bfloat16* __restrict__ x, const __nv_bfloat16* __restrict__ dw, const __nv_bfloat16* __restrict__ w1) {
    extern __shared__ __align__(1024) unsigned char smem[];
    unsigned char* s_w1 = smem;
    unsigned char* s_y = smem + 73728;
    float* s_dw = reinterpret_cast<float*>(smem + 73728 + NWG * 12288);
    float* s_red = s_dw + 128;

    const int tid = threadIdx.x;
    const int wg = tid >> 7;
    const int warp = (tid >> 5) & 3;
    const int lane = tid & 31;
    const int q = lane & 3;

    stage_w1_async(smem_u32(s_w1), w1, tid);
    cp_async_commit();
    const int nwg = gridDim.x * NWG;
    int tile = blockIdx.x * NWG + wg;
    XRows xn;
    if (tile < NTILES) load_x(xn, x, tile, warp, lane);
    if (tid < C_IN) s_dw[tid] = __bfloat162float(dw[tid]);
    for (int i = tid; i < C_H; i += NTHR) s_red[i] = 0.f;
    cp_async_wait_all();
    proxy_fence();
    __syncthreads();

    float ss[12];
#pragma unroll
    for (int i = 0; i < 12; i++) ss[i] = 0.f;

    unsigned char* ytile = s_y + wg * 12288;
    const uint64_t w1_desc = make_desc(smem_u32(s_w1), W1_LBO, W1_SBO);
    const uint64_t y_desc = make_desc(smem_u32(ytile), Y_LBO, Y_SBO);
    const int rl = warp * 16 + (lane >> 2);
    unsigned char* yp = ytile + (rl >> 3) * Y_SBO + q * Y_LBO + (rl & 7) * 16;
    for (; tile < NTILES; tile += nwg) {
        {
            uint4 y[3];
            ln_row4(xn.a, s_dw + 8 * q, y);
#pragma unroll
            for (int i = 0; i < 3; i++) *reinterpret_cast<uint4*>(yp + 4 * i * Y_LBO) = y[i];
            ln_row4(xn.b, s_dw + 8 * q, y);
#pragma unroll
            for (int i = 0; i < 3; i++) *reinterpret_cast<uint4*>(yp + Y_SBO + 4 * i * Y_LBO) = y[i];
        }
        proxy_fence();
        wg_bar(1 + wg);
        if (tile + nwg < NTILES) load_x(xn, x, tile + nwg, warp, lane);
        float S[2][32];
        wg_fence();
#pragma unroll
        for (int t = 0; t < 6; t++)
            wgmma_ss_n64_tA(S[0], w1_desc + ((2 * t * W1_LBO) >> 4), y_desc + ((2 * t * Y_LBO) >> 4), t != 0);
        wg_commit();
#pragma unroll
        for (int m = 0; m < 6; m++) {
            if (m + 1 < 6) {
                wg_fence();
#pragma unroll
                for (int t = 0; t < 6; t++)
                    wgmma_ss_n64_tA(S[(m + 1) & 1], w1_desc + (((m + 1) * 8 * W1_SBO + 2 * t * W1_LBO) >> 4),
                                    y_desc + ((2 * t * Y_LBO) >> 4), t != 0);
                wg_commit();
                wg_wait<1>();
            } else {
                wg_wait<0>();
            }
            float(&Sc)[32] = S[m & 1];
            float a0 = ss[2 * m], a1 = ss[2 * m + 1];
#pragma unroll
            for (int j = 0; j < 8; j++) {
                float g0 = gelu2(Sc[4 * j]);
                float g1 = gelu2(Sc[4 * j + 1]);
                float g2 = gelu2(Sc[4 * j + 2]);
                float g3 = gelu2(Sc[4 * j + 3]);
                a0 = fmaf(g0, g0, a0);
                a1 = fmaf(g2, g2, a1);
                a0 = fmaf(g1, g1, a0);
                a1 = fmaf(g3, g3, a1);
            }
            ss[2 * m] = a0;
            ss[2 * m + 1] = a1;
        }
        wg_bar(1 + wg);
    }
#pragma unroll
    for (int i = 0; i < 12; i++) {
        float v = ss[i];
        v += __shfl_xor_sync(0xffffffffu, v, 1);
        v += __shfl_xor_sync(0xffffffffu, v, 2);
        if (q == 0) {
            int m = i >> 1, hh = i & 1;
            atomicAdd(&s_red[m * 64 + warp * 16 + hh * 8 + (lane >> 2)], v);
        }
    }
    __syncthreads();
    const float sc = 0.25f / (GELU_KAPPA * GELU_KAPPA);
    for (int i = tid; i < C_H; i += NTHR) g_partial[blockIdx.x * C_H + i] = s_red[i] * sc;
}

__device__ __forceinline__ void fetch_x_tile(uint32_t ydst, const __nv_bfloat16* __restrict__ x, int tile, int rl, int q) {
    const __nv_bfloat16* src = x + ((size_t)tile * TILE_M + rl) * C_IN + q * 8;
#pragma unroll
    for (int i = 0; i < 3; i++) {
        cp_async16(ydst + 4 * i * Y_LBO, src + i * 32);
        cp_async16(ydst + Y_SBO + 4 * i * Y_LBO, src + 8 * C_IN + i * 32);
    }
    cp_async_commit();
}

__global__ void __launch_bounds__(NTHR, 1)
k_main(const __nv_bfloat16* __restrict__ x, const __nv_bfloat16* __restrict__ dw, const __nv_bfloat16* __restrict__ w1,
       const __nv_bfloat16* __restrict__ w2, const __nv_bfloat16* __restrict__ grn_g,
       const __nv_bfloat16* __restrict__ grn_b, __nv_bfloat16* __restrict__ out, int n_part) {
    extern __shared__ __align__(1024) unsigned char smem[];
    unsigned char* s_w1 = smem;
    unsigned char* s_w2 = smem + 73728;
    unsigned char* s_y = smem + 2 * 73728;
    float* s_dw = reinterpret_cast<float*>(smem + 2 * 73728 + NWG * 12288);
    float* s_c = s_dw + 128;
    float* s_s = s_c + 128;
    float* s_tmp = s_s + 384;

    const int tid = threadIdx.x;
    const int wg = tid >> 7;
    const int warp = (tid >> 5) & 3;
    const int lane = tid & 31;
    const int q = lane & 3;
    const int rl = warp * 16 + (lane >> 2);

    unsigned char* ytile = s_y + wg * 12288;
    unsigned char* yp = ytile + (rl >> 3) * Y_SBO + q * Y_LBO + (rl & 7) * 16;
    const uint32_t yp_u32 = smem_u32(yp);
    const int nwg = gridDim.x * NWG;
    int tile = blockIdx.x * NWG + wg;

    stage_w1_async(smem_u32(s_w1), w1, tid);
    cp_async_commit();
    if (tile < NTILES) fetch_x_tile(yp_u32, x, tile, rl, q);

    if (tid < C_IN) { s_dw[tid] = __bfloat162float(dw[tid]); s_c[tid] = 0.f; }
    float lsum = 0.f;
    for (int k = tid; k < C_H; k += NTHR) {
        float a = 0.f;
#pragma unroll 4
        for (int b = 0; b < n_part; b++) a += g_partial[b * C_H + k];
        float gx = sqrtf(a + 1e-6f);
        s_s[k] = gx;
        lsum += gx;
    }
#pragma unroll
    for (int o = 16; o > 0; o >>= 1) lsum += __shfl_xor_sync(0xffffffffu, lsum, o);
    if (lane == 0) s_tmp[tid >> 5] = lsum;
    __syncthreads();
    float tot = 0.f;
#pragma unroll
    for (int i = 0; i < NTHR / 32; i++) tot += s_tmp[i];
    float inv = 1.0f / (tot * (1.0f / C_H) + 1e-6f);
    __syncthreads();
    for (int k = tid; k < C_H; k += NTHR) {
        float nx = s_s[k] * inv;
        s_s[k] = (0.5f / GELU_KAPPA) * (1.0f + __bfloat162float(grn_g[k]) * nx);
    }
    {
        float a0 = 0.f, a1 = 0.f, a2 = 0.f;
        int kbase = (tid >> 5) * (C_H / (NTHR / 32));
#pragma unroll 8
        for (int k = kbase; k < kbase + C_H / (NTHR / 32); k++) {
            float b = __bfloat162float(grn_b[k]);
            a0 = fmaf(b, __bfloat162float(w2[k * C_IN + lane]), a0);
            a1 = fmaf(b, __bfloat162float(w2[k * C_IN + lane + 32]), a1);
            a2 = fmaf(b, __bfloat162float(w2[k * C_IN + lane + 64]), a2);
        }
        atomicAdd(&s_c[lane], a0);
        atomicAdd(&s_c[lane + 32], a1);
        atomicAdd(&s_c[lane + 64], a2);
    }
    __syncthreads();
    for (int it = tid; it < 384 * 3; it += NTHR) {
        int kr = it & 7;
        int grp = (it >> 3) % 3;
        int kb = (it >> 3) / 3;
        int k = kb * 8 + kr;
        float sk = s_s[k];
        const uint4* src = reinterpret_cast<const uint4*>(w2 + k * C_IN + grp * 32);
        uint32_t wv[4][4];
#pragma unroll
        for (int qq = 0; qq < 4; qq++) {
            uint4 v = __ldg(src + qq);
            wv[qq][0] = v.x; wv[qq][1] = v.y; wv[qq][2] = v.z; wv[qq][3] = v.w;
        }
#pragma unroll
        for (int jj = 0; jj < 4; jj++) {
            uint32_t o[4];
#pragma unroll
            for (int qq = 0; qq < 4; qq++) o[qq] = pack_bf16(sk * bf_lo(wv[qq][jj]), sk * bf_hi(wv[qq][jj]));
            *reinterpret_cast<uint4*>(s_w2 + (grp * 4 + jj) * W2_SBO + kb * W2_LBO + kr * 16) =
                make_uint4(o[0], o[1], o[2], o[3]);
        }
    }
    cp_async_wait_all();
    proxy_fence();
    __syncthreads();

    const uint64_t w1_desc = make_desc(smem_u32(s_w1), W1_LBO, W1_SBO);
    const uint64_t w2_desc = make_desc(smem_u32(s_w2), W2_LBO, W2_SBO);
    const uint64_t y_desc = make_desc(smem_u32(ytile), Y_LBO, Y_SBO);
    for (; tile < NTILES; tile += nwg) {
        const int ntile = tile + nwg;
        if (ntile < NTILES) {
            int t128 = tid & 127;
            if (t128 < 96) prefetch_l2(reinterpret_cast<const unsigned char*>(x + (size_t)ntile * TILE_M * C_IN) + t128 * 128);
        }
        {
            uint4 xv[3], y[3];
#pragma unroll
            for (int i = 0; i < 3; i++) xv[i] = *reinterpret_cast<const uint4*>(yp + 4 * i * Y_LBO);
            ln_row4(xv, s_dw + 8 * q, y);
#pragma unroll
            for (int i = 0; i < 3; i++) *reinterpret_cast<uint4*>(yp + 4 * i * Y_LBO) = y[i];
#pragma unroll
            for (int i = 0; i < 3; i++) xv[i] = *reinterpret_cast<const uint4*>(yp + Y_SBO + 4 * i * Y_LBO);
            ln_row4(xv, s_dw + 8 * q, y);
#pragma unroll
            for (int i = 0; i < 3; i++) *reinterpret_cast<uint4*>(yp + Y_SBO + 4 * i * Y_LBO) = y[i];
        }
        proxy_fence();
        wg_bar(1 + wg);

        float O[48];
#pragma unroll
        for (int j = 0; j < 12; j++) {
            float2 cc = *reinterpret_cast<const float2*>(&s_c[32 * (j >> 2) + 8 * q + 2 * (j & 3)]);
            O[4 * j] = cc.x; O[4 * j + 1] = cc.y; O[4 * j + 2] = cc.x; O[4 * j + 3] = cc.y;
        }
        float S[32];
        uint32_t hf[16];
        wg_fence();
#pragma unroll
        for (int t = 0; t < 6; t++)
            wgmma_ss_n64(S, y_desc + ((2 * t * Y_LBO) >> 4), w1_desc + ((2 * t * W1_LBO) >> 4), t != 0);
        wg_commit();
#pragma unroll
        for (int c = 0; c < 6; c++) {
            wg_wait<0>();
            if (c == 5) {
                wg_bar(1 + wg);
                if (ntile < NTILES) fetch_x_tile(yp_u32, x, ntile, rl, q);
            }
#pragma unroll
            for (int j = 0; j < 8; j++) {
                float g0 = gelu2(S[4 * j]);
                float g1 = gelu2(S[4 * j + 1]);
                float g2 = gelu2(S[4 * j + 2]);
                float g3 = gelu2(S[4 * j + 3]);
                hf[2 * j] = pack_bf16(g0, g1);
                hf[2 * j + 1] = pack_bf16(g2, g3);
            }
            wg_fence();
#pragma unroll
            for (int t = 0; t < 4; t++)
                wgmma_n96(O, hf[4 * t], hf[4 * t + 1], hf[4 * t + 2], hf[4 * t + 3],
                          w2_desc + (((c * 8 + 2 * t) * W2_LBO) >> 4));
            if (c + 1 < 6) {
#pragma unroll
                for (int t = 0; t < 6; t++)
                    wgmma_ss_n64(S, y_desc + ((2 * t * Y_LBO) >> 4),
                                 w1_desc + (((c + 1) * 8 * W1_SBO + 2 * t * W1_LBO) >> 4), t != 0);
            }
            wg_commit();
        }
        XRows xr;
        load_x(xr, x, tile, warp, lane);
        wg_wait<0>();
        int r0 = tile * TILE_M + rl;
        uint4* p0 = reinterpret_cast<uint4*>(out + (size_t)r0 * C_IN + q * 8);
        uint4* p1 = reinterpret_cast<uint4*>(out + (size_t)(r0 + 8) * C_IN + q * 8);
#pragma unroll
        for (int i = 0; i < 3; i++) {
            uint32_t wa[4] = {xr.a[i].x, xr.a[i].y, xr.a[i].z, xr.a[i].w};
            uint32_t wb[4] = {xr.b[i].x, xr.b[i].y, xr.b[i].z, xr.b[i].w};
            uint32_t oa[4], ob[4];
#pragma unroll
            for (int p = 0; p < 4; p++) {
                int j = i * 4 + p;
                oa[p] = pack_bf16(bf_lo(wa[p]) + O[4 * j], bf_hi(wa[p]) + O[4 * j + 1]);
                ob[p] = pack_bf16(bf_lo(wb[p]) + O[4 * j + 2], bf_hi(wb[p]) + O[4 * j + 3]);
            }
            p0[i * 4] = make_uint4(oa[0], oa[1], oa[2], oa[3]);
            p1[i * 4] = make_uint4(ob[0], ob[1], ob[2], ob[3]);
        }
        cp_async_wait_all();
    }
}

extern "C" void kernel_launch(void* const* d_in, const int* in_sizes, int n_in, void* d_out, int out_size) {
    const __nv_bfloat16* x = (const __nv_bfloat16*)d_in[0];
    const __nv_bfloat16* dw = (const __nv_bfloat16*)d_in[1];
    const __nv_bfloat16* w1 = (const __nv_bfloat16*)d_in[2];
    const __nv_bfloat16* w2 = (const __nv_bfloat16*)d_in[3];
    const __nv_bfloat16* grn_g = (const __nv_bfloat16*)d_in[4];
    const __nv_bfloat16* grn_b = (const __nv_bfloat16*)d_in[5];
    __nv_bfloat16* out = (__nv_bfloat16*)d_out;

    static int n_sm = 0;
    const int smem1 = 73728 + NWG * 12288 + 512 + 1536;
    const int smem2 = 2 * 73728 + NWG * 12288 + 512 + 512 + 1536 + 128;
    if (n_sm == 0) {
        int dev = 0;
        cudaGetDevice(&dev);
        cudaDeviceGetAttribute(&n_sm, cudaDevAttrMultiProcessorCount, dev);
        if (n_sm > MAX_CTAS) n_sm = MAX_CTAS;
        cudaFuncSetAttribute(k_stats, cudaFuncAttributeMaxDynamicSharedMemorySize, smem1);
        cudaFuncSetAttribute(k_main, cudaFuncAttributeMaxDynamicSharedMemorySize, smem2);
    }
    k_stats<<<n_sm, NTHR, smem1>>>(x, dw, w1);
    k_main<<<n_sm, NTHR, smem2>>>(x, dw, w1, w2, grn_g, grn_b, out, n_sm);
}
```

```cpp
#include <cuda_runtime.h>
#include <cuda_bf16.h>
#include <stdint.h>
#include <cuda.h>

#define C_IN 96
#define C_H 384
#define NROWS (512 * 512)
#define TILE_M 64
#define NTILES (NROWS / TILE_M)
#define MAX_CTAS 256
#define NWG 4
#define NTHR (NWG * 128)

__device__ float g_partial[MAX_CTAS * C_H];
#define TSTAMP(i)

#define GELU_KAPPA 0.3292034911525734f
#define GELU_C0K 2.423681954311584f

__device__ __forceinline__ uint32_t smem_u32(const void* p) { return (uint32_t)__cvta_generic_to_shared(p); }
__device__ __forceinline__ uint64_t make_desc(uint32_t addr, uint32_t lbo, uint32_t sbo, uint32_t swz = 0) {
    uint64_t d = 0;
    d |= (uint64_t)((addr & 0x3FFFF) >> 4);
    d |= (uint64_t)((lbo >> 4) & 0x3FFF) << 16;
    d |= (uint64_t)((sbo >> 4) & 0x3FFF) << 32;
    d |= (uint64_t)swz << 62;
    return d;
}
__device__ __forceinline__ void mbar_init(uint32_t bar, uint32_t count) {
    asm volatile("mbarrier.init.shared::cta.b64 [%0], %1;\n" ::"r"(bar), "r"(count) : "memory");
}
__device__ __forceinline__ void mbar_expect_tx(uint32_t bar, uint32_t bytes) {
    asm volatile("mbarrier.arrive.expect_tx.shared::cta.b64 _, [%0], %1;\n" ::"r"(bar), "r"(bytes) : "memory");
}
__device__ __forceinline__ void mbar_wait(uint32_t bar, uint32_t parity) {
    asm volatile(
        "{\n.reg .pred p;\n"
        "WAIT_LOOP:\n"
        "mbarrier.try_wait.parity.shared::cta.b64 p, [%0], %1;\n"
        "@p bra WAIT_DONE;\n"
        "bra WAIT_LOOP;\n"
        "WAIT_DONE:\n}\n" ::"r"(bar), "r"(parity) : "memory");
}
__device__ __forceinline__ void tma_load_2d(uint32_t dst, const CUtensorMap* tm, uint32_t bar, int c0, int c1) {
    asm volatile(
        "cp.async.bulk.tensor.2d.shared::cluster.global.mbarrier::complete_tx::bytes [%0], [%1, {%3, %4}], [%2];\n" ::"r"(dst),
        "l"(reinterpret_cast<uint64_t>(tm)), "r"(bar), "r"(c0), "r"(c1)
        : "memory");
}
__device__ __forceinline__ void wg_fence() { asm volatile("wgmma.fence.sync.aligned;\n" ::: "memory"); }
__device__ __forceinline__ void wg_commit() { asm volatile("wgmma.commit_group.sync.aligned;\n" ::: "memory"); }
template <int N>
__device__ __forceinline__ void wg_wait() { asm volatile("wgmma.wait_group.sync.aligned %0;\n" ::"n"(N) : "memory"); }
__device__ __forceinline__ void wg_bar(int id) { asm volatile("bar.sync %0, 128;" ::"r"(id) : "memory"); }
__device__ __forceinline__ void proxy_fence() {
 asm volatile("fence.proxy.async.shared::cta;\n" ::: "memory"); }
__device__ __forceinline__ void cp_async16(uint32_t dst, const void* src) {
    asm volatile("cp.async.cg.shared.global [%0], [%1], 16;\n" ::"r"(dst), "l"(src) : "memory");
}
__device__ __forceinline__ void cp_async_commit() { asm volatile("cp.async.commit_group;\n" ::: "memory"); }
__device__ __forceinline__ void cp_async_wait_all() { asm volatile("cp.async.wait_group 0;\n" ::: "memory"); }
__device__ __forceinline__ void prefetch_l2(const void* p) { asm volatile("prefetch.global.L2 [%0];\n" ::"l"(p)); }

__device__ __forceinline__ float tanh_approx(float x) {
    float y;
    asm("tanh.approx.f32 %0, %1;" : "=f"(y) : "f"(x));
    return y;
}
__device__ __forceinline__ uint32_t pack_bf16(float lo, float hi) {
    uint32_t r;
    asm("cvt.rn.bf16x2.f32 %0, %1, %2;" : "=r"(r) : "f"(hi), "f"(lo));
    return r;
}
__device__ __forceinline__ float bf_lo(uint32_t v) { return __uint_as_float(v << 16); }
__device__ __forceinline__ float bf_hi(uint32_t v) { return __uint_as_float(v & 0xffff0000u); }

#define ACC32(d)                                                                                             \
    "+f"(d[0]), "+f"(d[1]), "+f"(d[2]), "+f"(d[3]), "+f"(d[4]), "+f"(d[5]), "+f"(d[6]), "+f"(d[7]),          \
        "+f"(d[8]), "+f"(d[9]), "+f"(d[10]), "+f"(d[11]), "+f"(d[12]), "+f"(d[13]), "+f"(d[14]), "+f"(d[15]), \
        "+f"(d[16]), "+f"(d[17]), "+f"(d[18]), "+f"(d[19]), "+f"(d[20]), "+f"(d[21]), "+f"(d[22]),           \
        "+f"(d[23]), "+f"(d[24]), "+f"(d[25]), "+f"(d[26]), "+f"(d[27]), "+f"(d[28]), "+f"(d[29]),           \
        "+f"(d[30]), "+f"(d[31])
#define ACC32_STR                                                                \
    "{%0, %1, %2, %3, %4, %5, %6, %7, %8, %9, %10, %11, %12, %13, %14, %15, "    \
    " %16, %17, %18, %19, %20, %21, %22, %23, %24, %25, %26, %27, %28, %29, %30, %31}"

__device__ __forceinline__ void wgmma_ss_n64_tA(float (&d)[32], uint64_t adesc, uint64_t bdesc, int scale_d) {
    asm volatile(
        "{\n.reg .pred p;\nsetp.ne.b32 p, %34, 0;\n"
        "wgmma.mma_async.sync.aligned.m64n64k16.f32.bf16.bf16 " ACC32_STR ", %32, %33, p, 1, 1, 1, 0;\n}\n"
        : ACC32(d)
        : "l"(adesc), "l"(bdesc), "r"(scale_d));
}
__device__ __forceinline__ void wgmma_ss_n64(float (&d)[32], uint64_t adesc, uint64_t bdesc, int scale_d) {
    asm volatile(
        "{\n.reg .pred p;\nsetp.ne.b32 p, %34, 0;\n"
        "wgmma.mma_async.sync.aligned.m64n64k16.f32.bf16.bf16 " ACC32_STR ", %32, %33, p, 1, 1, 0, 1;\n}\n"
        : ACC32(d)
        : "l"(adesc), "l"(bdesc), "r"(scale_d));
}
__device__ __forceinline__ void wgmma_n96(float (&d)[48], uint32_t a0, uint32_t a1, uint32_t a2, uint32_t a3,
                                          uint64_t bdesc) {
    asm volatile(
        "{\n"
        "wgmma.mma_async.sync.aligned.m64n96k16.f32.bf16.bf16 "
        "{%0, %1, %2, %3, %4, %5, %6, %7, %8, %9, %10, %11, %12, %13, %14, %15, "
        " %16, %17, %18, %19, %20, %21, %22, %23, %24, %25, %26, %27, %28, %29, %30, %31, "
        " %32, %33, %34, %35, %36, %37, %38, %39, %40, %41, %42, %43, %44, %45, %46, %47}, "
        "{%48, %49, %50, %51}, %52, 1, 1, 1, 1;\n"
        "}\n"
        : ACC32(d), "+f"(d[32]), "+f"(d[33]), "+f"(d[34]), "+f"(d[35]), "+f"(d[36]), "+f"(d[37]), "+f"(d[38]),
          "+f"(d[39]), "+f"(d[40]), "+f"(d[41]), "+f"(d[42]), "+f"(d[43]), "+f"(d[44]), "+f"(d[45]), "+f"(d[46]),
          "+f"(d[47])
        : "r"(a0), "r"(a1), "r"(a2), "r"(a3), "l"(bdesc));
}

#define W2_LBO 128
#define W2_SBO (48 * 128)
#define W1_BOX_BYTES (96 * 128)
#define Y_BOX_BYTES (64 * 64)
#define Y_TILE_BYTES (3 * Y_BOX_BYTES)

__device__ __forceinline__ void ln_row4(const uint4 (&xv)[3], const float* __restrict__ s_dwq, uint4 (&y)[3]) {
    float xf[24], dwf[24];
    float s = 0.f;
#pragma unroll
    for (int i = 0; i < 3; i++) {
        uint32_t w[4] = {xv[i].x, xv[i].y, xv[i].z, xv[i].w};
        float4 da = *reinterpret_cast<const float4*>(s_dwq + 32 * i);
        float4 db = *reinterpret_cast<const float4*>(s_dwq + 32 * i + 4);
        dwf[i * 8 + 0] = da.x; dwf[i * 8 + 1] = da.y; dwf[i * 8 + 2] = da.z; dwf[i * 8 + 3] = da.w;
        dwf[i * 8 + 4] = db.x; dwf[i * 8 + 5] = db.y; dwf[i * 8 + 6] = db.z; dwf[i * 8 + 7] = db.w;
#pragma unroll
        for (int p = 0; p < 4; p++) {
            xf[i * 8 + 2 * p] = bf_lo(w[p]);
            xf[i * 8 + 2 * p + 1] = bf_hi(w[p]);
        }
#pragma unroll
        for (int p = 0; p < 8; p++) s = fmaf(xf[i * 8 + p], dwf[i * 8 + p], s);
    }
    s += __shfl_xor_sync(0xffffffffu, s, 1);
    s += __shfl_xor_sync(0xffffffffu, s, 2);
    float nmean = s * (-1.0f / C_IN);
    float v = 0.f;
#pragma unroll
    for (int i = 0; i < 24; i++) {
        xf[i] = fmaf(xf[i], dwf[i], nmean);
        v = fmaf(xf[i], xf[i], v);
    }
    v += __shfl_xor_sync(0xffffffffu, v, 1);
    v += __shfl_xor_sync(0xffffffffu, v, 2);
    float rstd = rsqrtf(v * (1.0f / C_IN) + 1e-5f) * GELU_KAPPA;
#pragma unroll
    for (int i = 0; i < 3; i++) {
        y[i].x = pack_bf16(xf[i * 8 + 0] * rstd, xf[i * 8 + 1] * rstd);
        y[i].y = pack_bf16(xf[i * 8 + 2] * rstd, xf[i * 8 + 3] * rstd);
        y[i].z = pack_bf16(xf[i * 8 + 4] * rstd, xf[i * 8 + 5] * rstd);
        y[i].w = pack_bf16(xf[i * 8 + 6] * rstd, xf[i * 8 + 7] * rstd);
    }
}

__device__ __forceinline__ void ln_tile_inplace(unsigned char* yp, const float* __restrict__ s_dwq) {
    uint4 xv[3], y[3];
#pragma unroll
    for (int i = 0; i < 3; i++) xv[i] = *reinterpret_cast<const uint4*>(yp + i * Y_BOX_BYTES);
    ln_row4(xv, s_dwq, y);
#pragma unroll
    for (int i = 0; i < 3; i++) *reinterpret_cast<uint4*>(yp + i * Y_BOX_BYTES) = y[i];
#pragma unroll
    for (int i = 0; i < 3; i++) xv[i] = *reinterpret_cast<const uint4*>(yp + 512 + i * Y_BOX_BYTES);
    ln_row4(xv, s_dwq, y);
#pragma unroll
    for (int i = 0; i < 3; i++) *reinterpret_cast<uint4*>(yp + 512 + i * Y_BOX_BYTES) = y[i];
}

__device__ __forceinline__ float gelu2(float u) {
    float t = fmaf(u, u, GELU_C0K);
    float a = t * u;
    float th = tanh_approx(a);
    return fmaf(u, th, u);
}

__device__ __forceinline__ void tma_x_tile(uint32_t dst, const CUtensorMap* tmx, uint32_t bar, int tile) {
    mbar_expect_tx(bar, Y_TILE_BYTES);
#pragma unroll
    for (int i = 0; i < 3; i++) tma_load_2d(dst + i * Y_BOX_BYTES, tmx, bar, i * 32, tile * TILE_M);
}

__global__ void __launch_bounds__(NTHR, 1)
k_stats(const __grid_constant__ CUtensorMap tm_x, const __grid_constant__ CUtensorMap tm_w1,
        const __nv_bfloat16* __restrict__ dw) {
    extern __shared__ __align__(1024) unsigned char smem[];
    unsigned char* s_w1 = smem;
    unsigned char* s_y = smem + 73728;
    float* s_dw = reinterpret_cast<float*>(smem + 73728 + NWG * 2 * Y_TILE_BYTES);
    float* s_red = s_dw + 128;
    uint64_t* s_bar = reinterpret_cast<uint64_t*>(s_red + C_H);

    const int tid = threadIdx.x;
    const int wg = tid >> 7;
    const int warp = (tid >> 5) & 3;
    const int lane = tid & 31;
    const int q = lane & 3;
    const int nwg = gridDim.x * NWG;
    int tile = blockIdx.x * NWG + wg;

    if (tid == 0) {
        for (int i = 0; i < 1 + 2 * NWG; i++) mbar_init(smem_u32(s_bar + i), 1);
        asm volatile("fence.mbarrier_init.release.cluster;\n" ::: "memory");
    }
    if (tid < C_IN) s_dw[tid] = __bfloat162float(dw[tid]);
    for (int i = tid; i < C_H; i += NTHR) s_red[i] = 0.f;
    __syncthreads();
    const uint32_t ybuf0 = smem_u32(s_y + wg * 2 * Y_TILE_BYTES);
    const uint32_t bar_y = smem_u32(s_bar + 1 + 2 * wg);
    if (tid == 0) {
        mbar_expect_tx(smem_u32(s_bar), 6 * W1_BOX_BYTES);
        for (int i = 0; i < 6; i++) tma_load_2d(smem_u32(s_w1) + i * W1_BOX_BYTES, &tm_w1, smem_u32(s_bar), i * 64, 0);
    }
    if ((tid & 127) == 0 && tile < NTILES) tma_x_tile(ybuf0, &tm_x, bar_y, tile);

    float ss[12];
#pragma unroll
    for (int i = 0; i < 12; i++) ss[i] = 0.f;

    const uint64_t w1_desc = make_desc(smem_u32(s_w1), W1_BOX_BYTES, 1024, 1);
    const int rl = warp * 16 + (lane >> 2);
    const int yoff = rl * 64 + ((q ^ ((rl >> 1) & 3)) * 16);
    mbar_wait(smem_u32(s_bar), 0);

    int it = 0;
    for (; tile < NTILES; tile += nwg, it++) {
        const int buf = it & 1;
        if ((tid & 127) == 0 && tile + nwg < NTILES) tma_x_tile(ybuf0 + (buf ^ 1) * Y_TILE_BYTES, &tm_x, bar_y + (buf ^ 1) * 8, tile + nwg);
        mbar_wait(bar_y + buf * 8, (it >> 1) & 1);
        unsigned char* ytile = s_y + (wg * 2 + buf) * Y_TILE_BYTES;
        ln_tile_inplace(ytile + yoff, s_dw + 8 * q);
        proxy_fence();
        wg_bar(1 + wg);
        const uint64_t y_desc = make_desc(smem_u32(ytile), 16, 512, 2);
        float S[2][32];
        wg_fence();
#pragma unroll
        for (int t = 0; t < 6; t++)
            wgmma_ss_n64_tA(S[0], w1_desc + ((t * 2048) >> 4), y_desc + (((t >> 1) * Y_BOX_BYTES + (t & 1) * 32) >> 4), t != 0);
        wg_commit();
#pragma unroll
        for (int m = 0; m < 6; m++) {
            if (m + 1 < 6) {
                wg_fence();
#pragma unroll
                for (int t = 0; t < 6; t++)
                    wgmma_ss_n64_tA(S[(m + 1) & 1], w1_desc + (((m + 1) * W1_BOX_BYTES + t * 2048) >> 4),
                                    y_desc + (((t >> 1) * Y_BOX_BYTES + (t & 1) * 32) >> 4), t != 0);
                wg_commit();
                wg_wait<1>();
            } else {
                wg_wait<0>();
            }
            float(&Sc)[32] = S[m & 1];
            float a0 = ss[2 * m], a1 = ss[2 * m + 1];
#pragma unroll
            for (int j = 0; j < 8; j++) {
                float g0 = gelu2(Sc[4 * j]);
                float g1 = gelu2(Sc[4 * j + 1]);
                float g2 = gelu2(Sc[4 * j + 2]);
                float g3 = gelu2(Sc[4 * j + 3]);
                a0 = fmaf(g0, g0, a0);
                a1 = fmaf(g2, g2, a1);
                a0 = fmaf(g1, g1, a0);
                a1 = fmaf(g3, g3, a1);
            }
            ss[2 * m] = a0;
            ss[2 * m + 1] = a1;
        }
        wg_bar(1 + wg);
    }
#pragma unroll
    for (int i = 0; i < 12; i++) {
        float v = ss[i];
        v += __shfl_xor_sync(0xffffffffu, v, 1);
        v += __shfl_xor_sync(0xffffffffu, v, 2);
        if (q == 0) {
            int m = i >> 1, hh = i & 1;
            atomicAdd(&s_red[m * 64 + warp * 16 + hh * 8 + (lane >> 2)], v);
        }
    }
    __syncthreads();
    const float sc = 0.25f / (GELU_KAPPA * GELU_KAPPA);
    for (int i = tid; i < C_H; i += NTHR) g_partial[blockIdx.x * C_H + i] = s_red[i] * sc;
}

struct XRows {
    uint4 a[3];
    uint4 b[3];
};
__device__ __forceinline__ void load_x(XRows& xr, const __nv_bfloat16* __restrict__ x, int tile, int warp, int lane) {
    int r0 = tile * TILE_M + warp * 16 + (lane >> 2);
    const uint4* p0 = reinterpret_cast<const uint4*>(x + (size_t)r0 * C_IN + (lane & 3) * 8);
    const uint4* p1 = reinterpret_cast<const uint4*>(x + (size_t)(r0 + 8) * C_IN + (lane & 3) * 8);
#pragma unroll
    for (int i = 0; i < 3; i++) {
        xr.a[i] = __ldg(p0 + i * 4);
        xr.b[i] = __ldg(p1 + i * 4);
    }
}

__global__ void __launch_bounds__(NTHR, 1)
k_main(const __grid_constant__ CUtensorMap tm_x, const __grid_constant__ CUtensorMap tm_w1,
       const __nv_bfloat16* __restrict__ x, const __nv_bfloat16* __restrict__ dw,
       const __nv_bfloat16* __restrict__ w2, const __nv_bfloat16* __restrict__ grn_g,
       const __nv_bfloat16* __restrict__ grn_b, __nv_bfloat16* __restrict__ out, int n_part) {
    extern __shared__ __align__(1024) unsigned char smem[];
    unsigned char* s_w1 = smem;
    unsigned char* s_w2 = smem + 73728;
    unsigned char* s_y = smem + 2 * 73728;
    float* s_dw = reinterpret_cast<float*>(smem + 2 * 73728 + NWG * Y_TILE_BYTES);
    float* s_c = s_dw + 128;
    float* s_s = s_c + 128;
    float* s_tmp = s_s + 384;
    uint64_t* s_bar = reinterpret_cast<uint64_t*>(s_tmp + 32);

    const int tid = threadIdx.x;
    const int wg = tid >> 7;
    const int warp = (tid >> 5) & 3;
    const int lane = tid & 31;
    const int q = lane & 3;
    const int rl = warp * 16 + (lane >> 2);
    const int nwg = gridDim.x * NWG;
    int tile = blockIdx.x * NWG + wg;

    unsigned char* ytile = s_y + wg * Y_TILE_BYTES;
    const uint32_t ytile_u = smem_u32(ytile);
    const uint32_t bar_y = smem_u32(s_bar + 1 + wg);
    if (tid == 0) {
        for (int i = 0; i < 1 + NWG; i++) mbar_init(smem_u32(s_bar + i), 1);
        asm volatile("fence.mbarrier_init.release.cluster;\n" ::: "memory");
    }
    if (tid < C_IN) { s_dw[tid] = __bfloat162float(dw[tid]); s_c[tid] = 0.f; }
    __syncthreads();
    if (tid == 0) {
        mbar_expect_tx(smem_u32(s_bar), 6 * W1_BOX_BYTES);
        for (int i = 0; i < 6; i++) tma_load_2d(smem_u32(s_w1) + i * W1_BOX_BYTES, &tm_w1, smem_u32(s_bar), i * 64, 0);
    }
    if ((tid & 127) == 0 && tile < NTILES) tma_x_tile(ytile_u, &tm_x, bar_y, tile);

    float lsum = 0.f;
    for (int k = tid; k < C_H; k += NTHR) {
        float a = 0.f;
#pragma unroll 4
        for (int b = 0; b < n_part; b++) a += g_partial[b * C_H + k];
        float gx = sqrtf(a + 1e-6f);
        s_s[k] = gx;
        lsum += gx;
    }
#pragma unroll
    for (int o = 16; o > 0; o >>= 1) lsum += __shfl_xor_sync(0xffffffffu, lsum, o);
    if (lane == 0) s_tmp[tid >> 5] = lsum;
    __syncthreads();
    float tot = 0.f;
#pragma unroll
    for (int i = 0; i < NTHR / 32; i++) tot += s_tmp[i];
    float inv = 1.0f / (tot * (1.0f / C_H) + 1e-6f);
    __syncthreads();
    for (int k = tid; k < C_H; k += NTHR) {
        float nx = s_s[k] * inv;
        s_s[k] = (0.5f / GELU_KAPPA) * (1.0f + __bfloat162float(grn_g[k]) * nx);
    }
    {
        float a0 = 0.f, a1 = 0.f, a2 = 0.f;
        int kbase = (tid >> 5) * (C_H / (NTHR / 32));
#pragma unroll 8
        for (int k = kbase; k < kbase + C_H / (NTHR / 32); k++) {
            float b = __bfloat162float(grn_b[k]);
            a0 = fmaf(b, __bfloat162float(w2[k * C_IN + lane]), a0);
            a1 = fmaf(b, __bfloat162float(w2[k * C_IN + lane + 32]), a1);
            a2 = fmaf(b, __bfloat162float(w2[k * C_IN + lane + 64]), a2);
        }
        atomicAdd(&s_c[lane], a0);
        atomicAdd(&s_c[lane + 32], a1);
        atomicAdd(&s_c[lane + 64], a2);
    }
    __syncthreads();
    for (int it = tid; it < 384 * 3; it += NTHR) {
        int kr = it & 7;
        int grp = (it >> 3) % 3;
        int kb = (it >> 3) / 3;
        int k = kb * 8 + kr;
        float sk = s_s[k];
        const uint4* src = reinterpret_cast<const uint4*>(w2 + k * C_IN + grp * 32);
        uint32_t wv[4][4];
#pragma unroll
        for (int qq = 0; qq < 4; qq++) {
            uint4 v = __ldg(src + qq);
            wv[qq][0] = v.x; wv[qq][1] = v.y; wv[qq][2] = v.z; wv[qq][3] = v.w;
        }
#pragma unroll
        for (int jj = 0; jj < 4; jj++) {
            uint32_t o[4];
#pragma unroll
            for (int qq = 0; qq < 4; qq++) o[qq] = pack_bf16(sk * bf_lo(wv[qq][jj]), sk * bf_hi(wv[qq][jj]));
            *reinterpret_cast<uint4*>(s_w2 + (grp * 4 + jj) * W2_SBO + kb * W2_LBO + kr * 16) =
                make_uint4(o[0], o[1], o[2], o[3]);
        }
    }
    proxy_fence();
    __syncthreads();
    mbar_wait(smem_u32(s_bar), 0);

    const uint64_t w1_desc = make_desc(smem_u32(s_w1), W1_BOX_BYTES, 1024, 1);
    const uint64_t w2_desc = make_desc(smem_u32(s_w2), W2_LBO, W2_SBO, 0);
    const uint64_t y_desc = make_desc(ytile_u, 16, 512, 2);
    unsigned char* yp = ytile + rl * 64 + ((q ^ ((rl >> 1) & 3)) * 16);
    int it = 0;
    for (; tile < NTILES; tile += nwg, it++) {
        const int ntile = tile + nwg;
        if (ntile < NTILES) {
            int t128 = tid & 127;
            if (t128 < 96) prefetch_l2(reinterpret_cast<const unsigned char*>(x + (size_t)ntile * TILE_M * C_IN) + t128 * 128);
        }
        mbar_wait(bar_y, it & 1);
        ln_tile_inplace(yp, s_dw + 8 * q);
        proxy_fence();
        wg_bar(1 + wg);

        float O[48];
#pragma unroll
        for (int j = 0; j < 12; j++) {
            float2 cc = *reinterpret_cast<const float2*>(&s_c[32 * (j >> 2) + 8 * q + 2 * (j & 3)]);
            O[4 * j] = cc.x; O[4 * j + 1] = cc.y; O[4 * j + 2] = cc.x; O[4 * j + 3] = cc.y;
        }
        float S[32];
        uint32_t hf[16];
        wg_fence();
#pragma unroll
        for (int t = 0; t < 6; t++)
            wgmma_ss_n64(S, y_desc + (((t >> 1) * Y_BOX_BYTES + (t & 1) * 32) >> 4), w1_desc + ((t * 2048) >> 4), t != 0);
        wg_commit();
#pragma unroll
        for (int c = 0; c < 6; c++) {
            wg_wait<0>();
            if (c == 5) {
                wg_bar(1 + wg);
                if ((tid & 127) == 0 && ntile < NTILES) tma_x_tile(ytile_u, &tm_x, bar_y, ntile);
            }
#pragma unroll
            for (int j = 0; j < 8; j++) {
                float g0 = gelu2(S[4 * j]);
                float g1 = gelu2(S[4 * j + 1]);
                float g2 = gelu2(S[4 * j + 2]);
                float g3 = gelu2(S[4 * j + 3]);
                hf[2 * j] = pack_bf16(g0, g1);
                hf[2 * j + 1] = pack_bf16(g2, g3);
            }
            wg_fence();
#pragma unroll
            for (int t = 0; t < 4; t++)
                wgmma_n96(O, hf[4 * t], hf[4 * t + 1], hf[4 * t + 2], hf[4 * t + 3],
                          w2_desc + (((c * 8 + 2 * t) * W2_LBO) >> 4));
            if (c + 1 < 6) {
#pragma unroll
                for (int t = 0; t < 6; t++)
                    wgmma_ss_n64(S, y_desc + (((t >> 1) * Y_BOX_BYTES + (t & 1) * 32) >> 4),
                                 w1_desc + (((c + 1) * W1_BOX_BYTES + t * 2048) >> 4), t != 0);
            }
            wg_commit();
        }
        XRows xr;
        load_x(xr, x, tile, warp, lane);
        wg_wait<0>();
        int r0 = tile * TILE_M + rl;
        uint4* p0 = reinterpret_cast<uint4*>(out + (size_t)r0 * C_IN + q * 8);
        uint4* p1 = reinterpret_cast<uint4*>(out + (size_t)(r0 + 8) * C_IN + q * 8);
#pragma unroll
        for (int i = 0; i < 3; i++) {
            uint32_t wa[4] = {xr.a[i].x, xr.a[i].y, xr.a[i].z, xr.a[i].w};
            uint32_t wb[4] = {xr.b[i].x, xr.b[i].y, xr.b[i].z, xr.b[i].w};
            uint32_t oa[4], ob[4];
#pragma unroll
            for (int p = 0; p < 4; p++) {
                int j = i * 4 + p;
                oa[p] = pack_bf16(bf_lo(wa[p]) + O[4 * j], bf_hi(wa[p]) + O[4 * j + 1]);
                ob[p] = pack_bf16(bf_lo(wb[p]) + O[4 * j + 2], bf_hi(wb[p]) + O[4 * j + 3]);
            }
            p0[i * 4] = make_uint4(oa[0], oa[1], oa[2], oa[3]);
            p1[i * 4] = make_uint4(ob[0], ob[1], ob[2], ob[3]);
        }
    }
}

#define SMEM1 (73728 + NWG * 2 * Y_TILE_BYTES + 512 + 1536 + 128)
#define SMEM2 (2 * 73728 + NWG * Y_TILE_BYTES + 512 + 512 + 1536 + 128 + 64)

typedef CUresult (*PFN_encodeTiled)(CUtensorMap*, CUtensorMapDataType, cuuint32_t, void*, const cuuint64_t*, const cuuint64_t*,
                                    const cuuint32_t*, const cuuint32_t*, CUtensorMapInterleave, CUtensorMapSwizzle,
                                    CUtensorMapL2promotion, CUtensorMapFloatOOBfill);

extern "C" void kernel_launch(void* const* d_in, const int* in_sizes, int n_in, void* d_out, int out_size) {
    const __nv_bfloat16* x = (const __nv_bfloat16*)d_in[0];
    const __nv_bfloat16* dw = (const __nv_bfloat16*)d_in[1];
    const __nv_bfloat16* w1 = (const __nv_bfloat16*)d_in[2];
    const __nv_bfloat16* w2 = (const __nv_bfloat16*)d_in[3];
    const __nv_bfloat16* grn_g = (const __nv_bfloat16*)d_in[4];
    const __nv_bfloat16* grn_b = (const __nv_bfloat16*)d_in[5];
    __nv_bfloat16* out = (__nv_bfloat16*)d_out;

    static int n_sm = 0;
    static CUtensorMap tm_x, tm_w1;
    static const void* last_x = nullptr;
    static const void* last_w1 = nullptr;
    static PFN_encodeTiled encode = nullptr;
    if (n_sm == 0) {
        int dev = 0;
        cudaGetDevice(&dev);
        cudaDeviceGetAttribute(&n_sm, cudaDevAttrMultiProcessorCount, dev);
        if (n_sm > MAX_CTAS) n_sm = MAX_CTAS;
        cudaFuncSetAttribute(k_stats, cudaFuncAttributeMaxDynamicSharedMemorySize, SMEM1);
        cudaFuncSetAttribute(k_main, cudaFuncAttributeMaxDynamicSharedMemorySize, SMEM2);
        cudaDriverEntryPointQueryResult qres;
        void* fn = nullptr;
        cudaGetDriverEntryPoint("cuTensorMapEncodeTiled", &fn, cudaEnableDefault, &qres);
        encode = (PFN_encodeTiled)fn;
    }
    if (last_x != x || last_w1 != w1) {
        {
            cuuint64_t dims[2] = {96, (cuuint64_t)NROWS};
            cuuint64_t strides[1] = {192};
            cuuint32_t box[2] = {32, 64};
            cuuint32_t es[2] = {1, 1};
            encode(&tm_x, CU_TENSOR_MAP_DATA_TYPE_BFLOAT16, 2, (void*)x, dims, strides, box, es, CU_TENSOR_MAP_INTERLEAVE_NONE,
                   CU_TENSOR_MAP_SWIZZLE_64B, CU_TENSOR_MAP_L2_PROMOTION_L2_128B, CU_TENSOR_MAP_FLOAT_OOB_FILL_NONE);
        }
        {
            cuuint64_t dims[2] = {384, 96};
            cuuint64_t strides[1] = {768};
            cuuint32_t box[2] = {64, 96};
            cuuint32_t es[2] = {1, 1};
            encode(&tm_w1, CU_TENSOR_MAP_DATA_TYPE_BFLOAT16, 2, (void*)w1, dims, strides, box, es, CU_TENSOR_MAP_INTERLEAVE_NONE,
                   CU_TENSOR_MAP_SWIZZLE_128B, CU_TENSOR_MAP_L2_PROMOTION_L2_128B, CU_TENSOR_MAP_FLOAT_OOB_FILL_NONE);
        }
        last_x = x;
        last_w1 = w1;
    }
    k_stats<<<n_sm, NTHR, SMEM1>>>(tm_x, tm_w1, dw);
    k_main<<<n_sm, NTHR, SMEM2>>>(tm_x, tm_w1, x, dw, w2, grn_g, grn_b, out, n_sm);
}
```

```cpp
#include <cuda_runtime.h>
#include <cuda_bf16.h>
#include <stdint.h>
#include <cuda.h>

#define C_IN 96
#define C_H 384
#define NROWS (512 * 512)
#define TILE_M 64
#define NTILES (NROWS / TILE_M)
#define MAX_CTAS 256
#define NWG 4
#define NTHR (NWG * 128)

__device__ float g_sum[C_H];
__device__ unsigned int g_done;
__device__ __align__(1024) unsigned char g_w2img[73728];
__device__ float g_c[C_IN];
#define TSTAMP(i)

#define GELU_KAPPA 0.3292034911525734f
#define GELU_C0K 2.423681954311584f

__device__ __forceinline__ uint32_t smem_u32(const void* p) { return (uint32_t)__cvta_generic_to_shared(p); }
__device__ __forceinline__ uint64_t make_desc(uint32_t addr, uint32_t lbo, uint32_t sbo, uint32_t swz = 0) {
    uint64_t d = 0;
    d |= (uint64_t)((addr & 0x3FFFF) >> 4);
    d |= (uint64_t)((lbo >> 4) & 0x3FFF) << 16;
    d |= (uint64_t)((sbo >> 4) & 0x3FFF) << 32;
    d |= (uint64_t)swz << 62;
    return d;
}
__device__ __forceinline__ void mbar_init(uint32_t bar, uint32_t count) {
    asm volatile("mbarrier.init.shared::cta.b64 [%0], %1;\n" ::"r"(bar), "r"(count) : "memory");
}
__device__ __forceinline__ void mbar_expect_tx(uint32_t bar, uint32_t bytes) {
    asm volatile("mbarrier.arrive.expect_tx.shared::cta.b64 _, [%0], %1;\n" ::"r"(bar), "r"(bytes) : "memory");
}
__device__ __forceinline__ void mbar_wait(uint32_t bar, uint32_t parity) {
    asm volatile(
        "{\n.reg .pred p;\n"
        "WAIT_LOOP:\n"
        "mbarrier.try_wait.parity.shared::cta.b64 p, [%0], %1;\n"
        "@p bra WAIT_DONE;\n"
        "bra WAIT_LOOP;\n"
        "WAIT_DONE:\n}\n" ::"r"(bar), "r"(parity) : "memory");
}
__device__ __forceinline__ void tma_load_2d(uint32_t dst, const CUtensorMap* tm, uint32_t bar, int c0, int c1) {
    asm volatile(
        "cp.async.bulk.tensor.2d.shared::cluster.global.mbarrier::complete_tx::bytes [%0], [%1, {%3, %4}], [%2];\n" ::"r"(dst),
        "l"(reinterpret_cast<uint64_t>(tm)), "r"(bar), "r"(c0), "r"(c1)
        : "memory");
}
__device__ __forceinline__ void wg_fence() { asm volatile("wgmma.fence.sync.aligned;\n" ::: "memory"); }
__device__ __forceinline__ void wg_commit() { asm volatile("wgmma.commit_group.sync.aligned;\n" ::: "memory"); }
template <int N>
__device__ __forceinline__ void wg_wait() { asm volatile("wgmma.wait_group.sync.aligned %0;\n" ::"n"(N) : "memory"); }
__device__ __forceinline__ void wg_bar(int id) { asm volatile("bar.sync %0, 128;" ::"r"(id) : "memory"); }
__device__ __forceinline__ void proxy_fence() {
 asm volatile("fence.proxy.async.shared::cta;\n" ::: "memory"); }
__device__ __forceinline__ void cp_async16(uint32_t dst, const void* src) {
    asm volatile("cp.async.cg.shared.global [%0], [%1], 16;\n" ::"r"(dst), "l"(src) : "memory");
}
__device__ __forceinline__ void cp_async_commit() { asm volatile("cp.async.commit_group;\n" ::: "memory"); }
__device__ __forceinline__ void cp_async_wait_all() { asm volatile("cp.async.wait_group 0;\n" ::: "memory"); }
__device__ __forceinline__ void prefetch_l2(const void* p) { asm volatile("prefetch.global.L2 [%0];\n" ::"l"(p)); }

__device__ __forceinline__ float tanh_approx(float x) {
    float y;
    asm("tanh.approx.f32 %0, %1;" : "=f"(y) : "f"(x));
    return y;
}
__device__ __forceinline__ uint32_t pack_bf16(float lo, float hi) {
    uint32_t r;
    asm("cvt.rn.bf16x2.f32 %0, %1, %2;" : "=r"(r) : "f"(hi), "f"(lo));
    return r;
}
__device__ __forceinline__ float bf_lo(uint32_t v) { return __uint_as_float(v << 16); }
__device__ __forceinline__ float bf_hi(uint32_t v) { return __uint_as_float(v & 0xffff0000u); }

#define ACC32(d)                                                                                             \
    "+f"(d[0]), "+f"(d[1]), "+f"(d[2]), "+f"(d[3]), "+f"(d[4]), "+f"(d[5]), "+f"(d[6]), "+f"(d[7]),          \
        "+f"(d[8]), "+f"(d[9]), "+f"(d[10]), "+f"(d[11]), "+f"(d[12]), "+f"(d[13]), "+f"(d[14]), "+f"(d[15]), \
        "+f"(d[16]), "+f"(d[17]), "+f"(d[18]), "+f"(d[19]), "+f"(d[20]), "+f"(d[21]), "+f"(d[22]),           \
        "+f"(d[23]), "+f"(d[24]), "+f"(d[25]), "+f"(d[26]), "+f"(d[27]), "+f"(d[28]), "+f"(d[29]),           \
        "+f"(d[30]), "+f"(d[31])
#define ACC32_STR                                                                \
    "{%0, %1, %2, %3, %4, %5, %6, %7, %8, %9, %10, %11, %12, %13, %14, %15, "    \
    " %16, %17, %18, %19, %20, %21, %22, %23, %24, %25, %26, %27, %28, %29, %30, %31}"

__device__ __forceinline__ void wgmma_ss_n64_tA(float (&d)[32], uint64_t adesc, uint64_t bdesc, int scale_d) {
    asm volatile(
        "{\n.reg .pred p;\nsetp.ne.b32 p, %34, 0;\n"
        "wgmma.mma_async.sync.aligned.m64n64k16.f32.bf16.bf16 " ACC32_STR ", %32, %33, p, 1, 1, 1, 0;\n}\n"
        : ACC32(d)
        : "l"(adesc), "l"(bdesc), "r"(scale_d));
}
__device__ __forceinline__ void wgmma_ss_n64(float (&d)[32], uint64_t adesc, uint64_t bdesc, int scale_d) {
    asm volatile(
        "{\n.reg .pred p;\nsetp.ne.b32 p, %34, 0;\n"
        "wgmma.mma_async.sync.aligned.m64n64k16.f32.bf16.bf16 " ACC32_STR ", %32, %33, p, 1, 1, 0, 1;\n}\n"
        : ACC32(d)
        : "l"(adesc), "l"(bdesc), "r"(scale_d));
}
__device__ __forceinline__ void wgmma_n96(float (&d)[48], uint32_t a0, uint32_t a1, uint32_t a2, uint32_t a3,
                                          uint64_t bdesc) {
    asm volatile(
        "{\n"
        "wgmma.mma_async.sync.aligned.m64n96k16.f32.bf16.bf16 "
        "{%0, %1, %2, %3, %4, %5, %6, %7, %8, %9, %10, %11, %12, %13, %14, %15, "
        " %16, %17, %18, %19, %20, %21, %22, %23, %24, %25, %26, %27, %28, %29, %30, %31, "
        " %32, %33, %34, %35, %36, %37, %38, %39, %40, %41, %42, %43, %44, %45, %46, %47}, "
        "{%48, %49, %50, %51}, %52, 1, 1, 1, 1;\n"
        "}\n"
        : ACC32(d), "+f"(d[32]), "+f"(d[33]), "+f"(d[34]), "+f"(d[35]), "+f"(d[36]), "+f"(d[37]), "+f"(d[38]),
          "+f"(d[39]), "+f"(d[40]), "+f"(d[41]), "+f"(d[42]), "+f"(d[43]), "+f"(d[44]), "+f"(d[45]), "+f"(d[46]),
          "+f"(d[47])
        : "r"(a0), "r"(a1), "r"(a2), "r"(a3), "l"(bdesc));
}

#define W2_LBO 128
#define W2_SBO (48 * 128)
#define W1_BOX_BYTES (96 * 128)
#define Y_BOX_BYTES (64 * 64)
#define Y_TILE_BYTES (3 * Y_BOX_BYTES)

__device__ __forceinline__ void ln_row4(const uint4 (&xv)[3], const float* __restrict__ s_dwq, uint4 (&y)[3]) {
    float xf[24], dwf[24];
    float s = 0.f;
#pragma unroll
    for (int i = 0; i < 3; i++) {
        uint32_t w[4] = {xv[i].x, xv[i].y, xv[i].z, xv[i].w};
        float4 da = *reinterpret_cast<const float4*>(s_dwq + 32 * i);
        float4 db = *reinterpret_cast<const float4*>(s_dwq + 32 * i + 4);
        dwf[i * 8 + 0] = da.x; dwf[i * 8 + 1] = da.y; dwf[i * 8 + 2] = da.z; dwf[i * 8 + 3] = da.w;
        dwf[i * 8 + 4] = db.x; dwf[i * 8 + 5] = db.y; dwf[i * 8 + 6] = db.z; dwf[i * 8 + 7] = db.w;
#pragma unroll
        for (int p = 0; p < 4; p++) {
            xf[i * 8 + 2 * p] = bf_lo(w[p]);
            xf[i * 8 + 2 * p + 1] = bf_hi(w[p]);
        }
#pragma unroll
        for (int p = 0; p < 8; p++) s = fmaf(xf[i * 8 + p], dwf[i * 8 + p], s);
    }
    s += __shfl_xor_sync(0xffffffffu, s, 1);
    s += __shfl_xor_sync(0xffffffffu, s, 2);
    float nmean = s * (-1.0f / C_IN);
    float v = 0.f;
#pragma unroll
    for (int i = 0; i < 24; i++) {
        xf[i] = fmaf(xf[i], dwf[i], nmean);
        v = fmaf(xf[i], xf[i], v);
    }
    v += __shfl_xor_sync(0xffffffffu, v, 1);
    v += __shfl_xor_sync(0xffffffffu, v, 2);
    float rstd = rsqrtf(v * (1.0f / C_IN) + 1e-5f) * GELU_KAPPA;
#pragma unroll
    for (int i = 0; i < 3; i++) {
        y[i].x = pack_bf16(xf[i * 8 + 0] * rstd, xf[i * 8 + 1] * rstd);
        y[i].y = pack_bf16(xf[i * 8 + 2] * rstd, xf[i * 8 + 3] * rstd);
        y[i].z = pack_bf16(xf[i * 8 + 4] * rstd, xf[i * 8 + 5] * rstd);
        y[i].w = pack_bf16(xf[i * 8 + 6] * rstd, xf[i * 8 + 7] * rstd);
    }
}

__device__ __forceinline__ void ln_tile_inplace(unsigned char* yp, const float* __restrict__ s_dwq) {
    uint4 xv[3], y[3];
#pragma unroll
    for (int i = 0; i < 3; i++) xv[i] = *reinterpret_cast<const uint4*>(yp + i * Y_BOX_BYTES);
    ln_row4(xv, s_dwq, y);
#pragma unroll
    for (int i = 0; i < 3; i++) *reinterpret_cast<uint4*>(yp + i * Y_BOX_BYTES) = y[i];
#pragma unroll
    for (int i = 0; i < 3; i++) xv[i] = *reinterpret_cast<const uint4*>(yp + 512 + i * Y_BOX_BYTES);
    ln_row4(xv, s_dwq, y);
#pragma unroll
    for (int i = 0; i < 3; i++) *reinterpret_cast<uint4*>(yp + 512 + i * Y_BOX_BYTES) = y[i];
}

__device__ __forceinline__ float gelu2(float u) {
    float t = fmaf(u, u, GELU_C0K);
    float a = t * u;
    float th = tanh_approx(a);
    return fmaf(u, th, u);
}

__device__ __forceinline__ void tma_x_tile(uint32_t dst, const CUtensorMap* tmx, uint32_t bar, int tile) {
    mbar_expect_tx(bar, Y_TILE_BYTES);
#pragma unroll
    for (int i = 0; i < 3; i++) tma_load_2d(dst + i * Y_BOX_BYTES, tmx, bar, i * 32, tile * TILE_M);
}

__global__ void __launch_bounds__(NTHR, 1)
k_stats(const __grid_constant__ CUtensorMap tm_x, const __grid_constant__ CUtensorMap tm_w1,
        const __nv_bfloat16* __restrict__ dw, const __nv_bfloat16* __restrict__ w2,
        const __nv_bfloat16* __restrict__ grn_g, const __nv_bfloat16* __restrict__ grn_b) {
    extern __shared__ __align__(1024) unsigned char smem[];
    unsigned char* s_w1 = smem;
    unsigned char* s_y = smem + 73728;
    float* s_dw = reinterpret_cast<float*>(smem + 73728 + NWG * 2 * Y_TILE_BYTES);
    float* s_red = s_dw + 128;
    uint64_t* s_bar = reinterpret_cast<uint64_t*>(s_red + C_H);

    const int tid = threadIdx.x;
    const int wg = tid >> 7;
    const int warp = (tid >> 5) & 3;
    const int lane = tid & 31;
    const int q = lane & 3;
    const int nwg = gridDim.x * NWG;
    int tile = blockIdx.x * NWG + wg;

    if (tid == 0) {
        for (int i = 0; i < 1 + 2 * NWG; i++) mbar_init(smem_u32(s_bar + i), 1);
        asm volatile("fence.mbarrier_init.release.cluster;\n" ::: "memory");
    }
    if (tid < C_IN) s_dw[tid] = __bfloat162float(dw[tid]);
    for (int i = tid; i < C_H; i += NTHR) s_red[i] = 0.f;
    __syncthreads();
    const uint32_t ybuf0 = smem_u32(s_y + wg * 2 * Y_TILE_BYTES);
    const uint32_t bar_y = smem_u32(s_bar + 1 + 2 * wg);
    if (tid == 0) {
        mbar_expect_tx(smem_u32(s_bar), 6 * W1_BOX_BYTES);
        for (int i = 0; i < 6; i++) tma_load_2d(smem_u32(s_w1) + i * W1_BOX_BYTES, &tm_w1, smem_u32(s_bar), i * 64, 0);
    }
    if ((tid & 127) == 0 && tile < NTILES) tma_x_tile(ybuf0, &tm_x, bar_y, tile);

    float ss[12];
#pragma unroll
    for (int i = 0; i < 12; i++) ss[i] = 0.f;

    const uint64_t w1_desc = make_desc(smem_u32(s_w1), W1_BOX_BYTES, 1024, 1);
    const int rl = warp * 16 + (lane >> 2);
    const int yoff = rl * 64 + ((q ^ ((rl >> 1) & 3)) * 16);
    mbar_wait(smem_u32(s_bar), 0);

    int it = 0;
    for (; tile < NTILES; tile += nwg, it++) {
        const int buf = it & 1;
        if ((tid & 127) == 0 && tile + nwg < NTILES) tma_x_tile(ybuf0 + (buf ^ 1) * Y_TILE_BYTES, &tm_x, bar_y + (buf ^ 1) * 8, tile + nwg);
        mbar_wait(bar_y + buf * 8, (it >> 1) & 1);
        unsigned char* ytile = s_y + (wg * 2 + buf) * Y_TILE_BYTES;
        ln_tile_inplace(ytile + yoff, s_dw + 8 * q);
        proxy_fence();
        wg_bar(1 + wg);
        const uint64_t y_desc = make_desc(smem_u32(ytile), 16, 512, 2);
        float S[2][32];
        wg_fence();
#pragma unroll
        for (int t = 0; t < 6; t++)
            wgmma_ss_n64_tA(S[0], w1_desc + ((t * 2048) >> 4), y_desc + (((t >> 1) * Y_BOX_BYTES + (t & 1) * 32) >> 4), t != 0);
        wg_commit();
#pragma unroll
        for (int m = 0; m < 6; m++) {
            if (m + 1 < 6) {
                wg_fence();
#pragma unroll
                for (int t = 0; t < 6; t++)
                    wgmma_ss_n64_tA(S[(m + 1) & 1], w1_desc + (((m + 1) * W1_BOX_BYTES + t * 2048) >> 4),
                                    y_desc + (((t >> 1) * Y_BOX_BYTES + (t & 1) * 32) >> 4), t != 0);
                wg_commit();
                wg_wait<1>();
            } else {
                wg_wait<0>();
            }
            float(&Sc)[32] = S[m & 1];
            float a0 = ss[2 * m], a1 = ss[2 * m + 1];
#pragma unroll
            for (int j = 0; j < 8; j++) {
                float g0 = gelu2(Sc[4 * j]);
                float g1 = gelu2(Sc[4 * j + 1]);
                float g2 = gelu2(Sc[4 * j + 2]);
                float g3 = gelu2(Sc[4 * j + 3]);
                a0 = fmaf(g0, g0, a0);
                a1 = fmaf(g2, g2, a1);
                a0 = fmaf(g1, g1, a0);
                a1 = fmaf(g3, g3, a1);
            }
            ss[2 * m] = a0;
            ss[2 * m + 1] = a1;
        }
        wg_bar(1 + wg);
    }
#pragma unroll
    for (int i = 0; i < 12; i++) {
        float v = ss[i];
        v += __shfl_xor_sync(0xffffffffu, v, 1);
        v += __shfl_xor_sync(0xffffffffu, v, 2);
        if (q == 0) {
            int m = i >> 1, hh = i & 1;
            atomicAdd(&s_red[m * 64 + warp * 16 + hh * 8 + (lane >> 2)], v);
        }
    }
    __syncthreads();
    const float sc = 0.25f / (GELU_KAPPA * GELU_KAPPA);
    for (int i = tid; i < C_H; i += NTHR) atomicAdd(&g_sum[i], s_red[i] * sc);
    __threadfence();
    __syncthreads();
    __shared__ unsigned int s_last;
    if (tid == 0) s_last = (atomicAdd(&g_done, 1u) == gridDim.x - 1);
    __syncthreads();
    if (!s_last) return;
    __threadfence();
    float* s_s = s_red;
    float* s_tmp = s_dw;
    float lsum = 0.f;
    if (tid < C_H) {
        float gx = sqrtf(__ldcg(&g_sum[tid]) + 1e-6f);
        g_sum[tid] = 0.f;
        s_s[tid] = gx;
        lsum = gx;
    }
#pragma unroll
    for (int o = 16; o > 0; o >>= 1) lsum += __shfl_xor_sync(0xffffffffu, lsum, o);
    if (lane == 0) s_tmp[tid >> 5] = lsum;
    if (tid == 0) g_done = 0;
    __syncthreads();
    float tot = 0.f;
#pragma unroll
    for (int i = 0; i < NTHR / 32; i++) tot += s_tmp[i];
    float inv = 1.0f / (tot * (1.0f / C_H) + 1e-6f);
    __syncthreads();
    if (tid < C_H) s_s[tid] = (0.5f / GELU_KAPPA) * (1.0f + __bfloat162float(grn_g[tid]) * (s_s[tid] * inv));
    if (tid < C_IN) s_tmp[tid] = 0.f;
    __syncthreads();
    {
        float a0 = 0.f, a1 = 0.f, a2 = 0.f;
        int kbase = (tid >> 5) * (C_H / (NTHR / 32));
#pragma unroll
        for (int k = kbase; k < kbase + C_H / (NTHR / 32); k++) {
            float b = __bfloat162float(grn_b[k]);
            a0 = fmaf(b, __bfloat162float(w2[k * C_IN + lane]), a0);
            a1 = fmaf(b, __bfloat162float(w2[k * C_IN + lane + 32]), a1);
            a2 = fmaf(b, __bfloat162float(w2[k * C_IN + lane + 64]), a2);
        }
        atomicAdd(&s_tmp[lane], a0);
        atomicAdd(&s_tmp[lane + 32], a1);
        atomicAdd(&s_tmp[lane + 64], a2);
    }
    for (int it2 = tid; it2 < 384 * 3; it2 += NTHR) {
        int kr = it2 & 7;
        int grp = (it2 >> 3) % 3;
        int kb = (it2 >> 3) / 3;
        int k = kb * 8 + kr;
        float sk = s_s[k];
        const uint4* src = reinterpret_cast<const uint4*>(w2 + k * C_IN + grp * 32);
        uint32_t wv[4][4];
#pragma unroll
        for (int qq = 0; qq < 4; qq++) {
            uint4 v = __ldg(src + qq);
            wv[qq][0] = v.x; wv[qq][1] = v.y; wv[qq][2] = v.z; wv[qq][3] = v.w;
        }
#pragma unroll
        for (int jj = 0; jj < 4; jj++) {
            uint32_t o[4];
#pragma unroll
            for (int qq = 0; qq < 4; qq++) o[qq] = pack_bf16(sk * bf_lo(wv[qq][jj]), sk * bf_hi(wv[qq][jj]));
            *reinterpret_cast<uint4*>(g_w2img + (grp * 4 + jj) * W2_SBO + kb * W2_LBO + kr * 16) =
                make_uint4(o[0], o[1], o[2], o[3]);
        }
    }
    __syncthreads();
    if (tid < C_IN) g_c[tid] = s_tmp[tid];
}

struct XRows {
    uint4 a[3];
    uint4 b[3];
};
__device__ __forceinline__ void load_x(XRows& xr, const __nv_bfloat16* __restrict__ x, int tile, int warp, int lane) {
    int r0 = tile * TILE_M + warp * 16 + (lane >> 2);
    const uint4* p0 = reinterpret_cast<const uint4*>(x + (size_t)r0 * C_IN + (lane & 3) * 8);
    const uint4* p1 = reinterpret_cast<const uint4*>(x + (size_t)(r0 + 8) * C_IN + (lane & 3) * 8);
#pragma unroll
    for (int i = 0; i < 3; i++) {
        xr.a[i] = __ldg(p0 + i * 4);
        xr.b[i] = __ldg(p1 + i * 4);
    }
}

__global__ void __launch_bounds__(NTHR, 1)
k_main(const __grid_constant__ CUtensorMap tm_x, const __grid_constant__ CUtensorMap tm_w1,
       const __nv_bfloat16* __restrict__ x, const __nv_bfloat16* __restrict__ dw, __nv_bfloat16* __restrict__ out) {
    extern __shared__ __align__(1024) unsigned char smem[];
    unsigned char* s_w1 = smem;
    unsigned char* s_w2 = smem + 73728;
    unsigned char* s_y = smem + 2 * 73728;
    float* s_dw = reinterpret_cast<float*>(smem + 2 * 73728 + NWG * Y_TILE_BYTES);
    float* s_c = s_dw + 128;
    float* s_s = s_c + 128;
    float* s_tmp = s_s + 384;
    uint64_t* s_bar = reinterpret_cast<uint64_t*>(s_tmp + 32);

    const int tid = threadIdx.x;
    const int wg = tid >> 7;
    const int warp = (tid >> 5) & 3;
    const int lane = tid & 31;
    const int q = lane & 3;
    const int rl = warp * 16 + (lane >> 2);
    const int nwg = gridDim.x * NWG;
    int tile = blockIdx.x * NWG + wg;

    unsigned char* ytile = s_y + wg * Y_TILE_BYTES;
    const uint32_t ytile_u = smem_u32(ytile);
    const uint32_t bar_y = smem_u32(s_bar + 1 + wg);
    if (tid == 0) {
        for (int i = 0; i < 1 + NWG; i++) mbar_init(smem_u32(s_bar + i), 1);
        asm volatile("fence.mbarrier_init.release.cluster;\n" ::: "memory");
    }
    if (tid < C_IN) { s_dw[tid] = __bfloat162float(dw[tid]); s_c[tid] = g_c[tid]; }
    __syncthreads();
    if (tid == 0) {
        mbar_expect_tx(smem_u32(s_bar), 6 * W1_BOX_BYTES + 73728);
        for (int i = 0; i < 6; i++) tma_load_2d(smem_u32(s_w1) + i * W1_BOX_BYTES, &tm_w1, smem_u32(s_bar), i * 64, 0);
        for (int i = 0; i < 6; i++)
            asm volatile("cp.async.bulk.shared::cluster.global.mbarrier::complete_tx::bytes [%0], [%1], %2, [%3];\n" ::"r"(
                             smem_u32(s_w2) + i * 12288),
                         "l"(g_w2img + i * 12288), "r"(12288), "r"(smem_u32(s_bar))
                         : "memory");
    }
    if ((tid & 127) == 0 && tile < NTILES) tma_x_tile(ytile_u, &tm_x, bar_y, tile);
    mbar_wait(smem_u32(s_bar), 0);

    const uint64_t w1_desc = make_desc(smem_u32(s_w1), W1_BOX_BYTES, 1024, 1);
    const uint64_t w2_desc = make_desc(smem_u32(s_w2), W2_LBO, W2_SBO, 0);
    const uint64_t y_desc = make_desc(ytile_u, 16, 512, 2);
    unsigned char* yp = ytile + rl * 64 + ((q ^ ((rl >> 1) & 3)) * 16);
    int it = 0;
    for (; tile < NTILES; tile += nwg, it++) {
        const int ntile = tile + nwg;
        if (ntile < NTILES) {
            int t128 = tid & 127;
            if (t128 < 96) prefetch_l2(reinterpret_cast<const unsigned char*>(x + (size_t)ntile * TILE_M * C_IN) + t128 * 128);
        }
        mbar_wait(bar_y, it & 1);
        ln_tile_inplace(yp, s_dw + 8 * q);
        proxy_fence();
        wg_bar(1 + wg);

        float O[48];
#pragma unroll
        for (int j = 0; j < 12; j++) {
            float2 cc = *reinterpret_cast<const float2*>(&s_c[32 * (j >> 2) + 8 * q + 2 * (j & 3)]);
            O[4 * j] = cc.x; O[4 * j + 1] = cc.y; O[4 * j + 2] = cc.x; O[4 * j + 3] = cc.y;
        }
        float S[32];
        uint32_t hf[16];
        wg_fence();
#pragma unroll
        for (int t = 0; t < 6; t++)
            wgmma_ss_n64(S, y_desc + (((t >> 1) * Y_BOX_BYTES + (t & 1) * 32) >> 4), w1_desc + ((t * 2048) >> 4), t != 0);
        wg_commit();
#pragma unroll
        for (int c = 0; c < 6; c++) {
            wg_wait<0>();
            if (c == 5) {
                wg_bar(1 + wg);
                if ((tid & 127) == 0 && ntile < NTILES) tma_x_tile(ytile_u, &tm_x, bar_y, ntile);
            }
#pragma unroll
            for (int j = 0; j < 8; j++) {
                float g0 = gelu2(S[4 * j]);
                float g1 = gelu2(S[4 * j + 1]);
                float g2 = gelu2(S[4 * j + 2]);
                float g3 = gelu2(S[4 * j + 3]);
                hf[2 * j] = pack_bf16(g0, g1);
                hf[2 * j + 1] = pack_bf16(g2, g3);
            }
            wg_fence();
#pragma unroll
            for (int t = 0; t < 4; t++)
                wgmma_n96(O, hf[4 * t], hf[4 * t + 1], hf[4 * t + 2], hf[4 * t + 3],
                          w2_desc + (((c * 8 + 2 * t) * W2_LBO) >> 4));
            if (c + 1 < 6) {
#pragma unroll
                for (int t = 0; t < 6; t++)
                    wgmma_ss_n64(S, y_desc + (((t >> 1) * Y_BOX_BYTES + (t & 1) * 32) >> 4),
                                 w1_desc + (((c + 1) * W1_BOX_BYTES + t * 2048) >> 4), t != 0);
            }
            wg_commit();
        }
        XRows xr;
        load_x(xr, x, tile, warp, lane);
        wg_wait<0>();
        int r0 = tile * TILE_M + rl;
        uint4* p0 = reinterpret_cast<uint4*>(out + (size_t)r0 * C_IN + q * 8);
        uint4* p1 = reinterpret_cast<uint4*>(out + (size_t)(r0 + 8) * C_IN + q * 8);
#pragma unroll
        for (int i = 0; i < 3; i++) {
            uint32_t wa[4] = {xr.a[i].x, xr.a[i].y, xr.a[i].z, xr.a[i].w};
            uint32_t wb[4] = {xr.b[i].x, xr.b[i].y, xr.b[i].z, xr.b[i].w};
            uint32_t oa[4], ob[4];
#pragma unroll
            for (int p = 0; p < 4; p++) {
                int j = i * 4 + p;
                oa[p] = pack_bf16(bf_lo(wa[p]) + O[4 * j], bf_hi(wa[p]) + O[4 * j + 1]);
                ob[p] = pack_bf16(bf_lo(wb[p]) + O[4 * j + 2], bf_hi(wb[p]) + O[4 * j + 3]);
            }
            p0[i * 4] = make_uint4(oa[0], oa[1], oa[2], oa[3]);
            p1[i * 4] = make_uint4(ob[0], ob[1], ob[2], ob[3]);
        }
    }
}

#define SMEM1 (73728 + NWG * 2 * Y_TILE_BYTES + 512 + 1536 + 128)
#define SMEM2 (2 * 73728 + NWG * Y_TILE_BYTES + 512 + 512 + 1536 + 128 + 64)

typedef CUresult (*PFN_encodeTiled)(CUtensorMap*, CUtensorMapDataType, cuuint32_t, void*, const cuuint64_t*, const cuuint64_t*,
                                    const cuuint32_t*, const cuuint32_t*, CUtensorMapInterleave, CUtensorMapSwizzle,
                                    CUtensorMapL2promotion, CUtensorMapFloatOOBfill);

extern "C" void kernel_launch(void* const* d_in, const int* in_sizes, int n_in, void* d_out, int out_size) {
    const __nv_bfloat16* x = (const __nv_bfloat16*)d_in[0];
    const __nv_bfloat16* dw = (const __nv_bfloat16*)d_in[1];
    const __nv_bfloat16* w1 = (const __nv_bfloat16*)d_in[2];
    const __nv_bfloat16* w2 = (const __nv_bfloat16*)d_in[3];
    const __nv_bfloat16* grn_g = (const __nv_bfloat16*)d_in[4];
    const __nv_bfloat16* grn_b = (const __nv_bfloat16*)d_in[5];
    __nv_bfloat16* out = (__nv_bfloat16*)d_out;

    static int n_sm = 0;
    static CUtensorMap tm_x, tm_w1;
    static const void* last_x = nullptr;
    static const void* last_w1 = nullptr;
    static PFN_encodeTiled encode = nullptr;
    if (n_sm == 0) {
        int dev = 0;
        cudaGetDevice(&dev);
        cudaDeviceGetAttribute(&n_sm, cudaDevAttrMultiProcessorCount, dev);
        if (n_sm > MAX_CTAS) n_sm = MAX_CTAS;
        cudaFuncSetAttribute(k_stats, cudaFuncAttributeMaxDynamicSharedMemorySize, SMEM1);
        cudaFuncSetAttribute(k_main, cudaFuncAttributeMaxDynamicSharedMemorySize, SMEM2);
        cudaDriverEntryPointQueryResult qres;
        void* fn = nullptr;
        cudaGetDriverEntryPoint("cuTensorMapEncodeTiled", &fn, cudaEnableDefault, &qres);
        encode = (PFN_encodeTiled)fn;
    }
    if (last_x != x || last_w1 != w1) {
        {
            cuuint64_t dims[2] = {96, (cuuint64_t)NROWS};
            cuuint64_t strides[1] = {192};
            cuuint32_t box[2] = {32, 64};
            cuuint32_t es[2] = {1, 1};
            encode(&tm_x, CU_TENSOR_MAP_DATA_TYPE_BFLOAT16, 2, (void*)x, dims, strides, box, es, CU_TENSOR_MAP_INTERLEAVE_NONE,
                   CU_TENSOR_MAP_SWIZZLE_64B, CU_TENSOR_MAP_L2_PROMOTION_L2_128B, CU_TENSOR_MAP_FLOAT_OOB_FILL_NONE);
        }
        {
            cuuint64_t dims[2] = {384, 96};
            cuuint64_t strides[1] = {768};
            cuuint32_t box[2] = {64, 96};
            cuuint32_t es[2] = {1, 1};
            encode(&tm_w1, CU_TENSOR_MAP_DATA_TYPE_BFLOAT16, 2, (void*)w1, dims, strides, box, es, CU_TENSOR_MAP_INTERLEAVE_NONE,
                   CU_TENSOR_MAP_SWIZZLE_128B, CU_TENSOR_MAP_L2_PROMOTION_L2_128B, CU_TENSOR_MAP_FLOAT_OOB_FILL_NONE);
        }
        last_x = x;
        last_w1 = w1;
    }
    k_stats<<<n_sm, NTHR, SMEM1>>>(tm_x, tm_w1, dw, w2, grn_g, grn_b);
    k_main<<<n_sm, NTHR, SMEM2>>>(tm_x, tm_w1, x, dw, out);
}
```

```cpp
#include <cuda_runtime.h>
#include <cuda_bf16.h>
#include <stdint.h>
#include <cuda.h>

#define C_IN 96
#define C_H 384
#define NROWS (512 * 512)
#define TILE_M 64
#define NTILES (NROWS / TILE_M)
#define MAX_CTAS 256
#define NWG 4
#define NTHR (NWG * 128)

__device__ float g_sum[C_H];
__device__ unsigned int g_done;
__device__ __align__(1024) unsigned char g_w2img[73728];
__device__ float g_c[C_IN];
#define TSTAMP(i)

#define GELU_KAPPA 0.3292034911525734f
#define GELU_C0K 2.423681954311584f

__device__ __forceinline__ uint32_t smem_u32(const void* p) { return (uint32_t)__cvta_generic_to_shared(p); }
__device__ __forceinline__ uint64_t make_desc(uint32_t addr, uint32_t lbo, uint32_t sbo, uint32_t swz = 0) {
    uint64_t d = 0;
    d |= (uint64_t)((addr & 0x3FFFF) >> 4);
    d |= (uint64_t)((lbo >> 4) & 0x3FFF) << 16;
    d |= (uint64_t)((sbo >> 4) & 0x3FFF) << 32;
    d |= (uint64_t)swz << 62;
    return d;
}
__device__ __forceinline__ void mbar_init(uint32_t bar, uint32_t count) {
    asm volatile("mbarrier.init.shared::cta.b64 [%0], %1;\n" ::"r"(bar), "r"(count) : "memory");
}
__device__ __forceinline__ void mbar_expect_tx(uint32_t bar, uint32_t bytes) {
    asm volatile("mbarrier.arrive.expect_tx.shared::cta.b64 _, [%0], %1;\n" ::"r"(bar), "r"(bytes) : "memory");
}
__device__ __forceinline__ void mbar_wait(uint32_t bar, uint32_t parity) {
    asm volatile(
        "{\n.reg .pred p;\n"
        "WAIT_LOOP:\n"
        "mbarrier.try_wait.parity.shared::cta.b64 p, [%0], %1;\n"
        "@p bra WAIT_DONE;\n"
        "bra WAIT_LOOP;\n"
        "WAIT_DONE:\n}\n" ::"r"(bar), "r"(parity) : "memory");
}
__device__ __forceinline__ void tma_load_2d(uint32_t dst, const CUtensorMap* tm, uint32_t bar, int c0, int c1) {
    asm volatile(
        "cp.async.bulk.tensor.2d.shared::cluster.global.mbarrier::complete_tx::bytes [%0], [%1, {%3, %4}], [%2];\n" ::"r"(dst),
        "l"(reinterpret_cast<uint64_t>(tm)), "r"(bar), "r"(c0), "r"(c1)
        : "memory");
}
__device__ __forceinline__ void wg_fence() { asm volatile("wgmma.fence.sync.aligned;\n" ::: "memory"); }
__device__ __forceinline__ void wg_commit() { asm volatile("wgmma.commit_group.sync.aligned;\n" ::: "memory"); }
template <int N>
__device__ __forceinline__ void wg_wait() { asm volatile("wgmma.wait_group.sync.aligned %0;\n" ::"n"(N) : "memory"); }
__device__ __forceinline__ void wg_bar(int id) { asm volatile("bar.sync %0, 128;" ::"r"(id) : "memory"); }
__device__ __forceinline__ void proxy_fence() {
 asm volatile("fence.proxy.async.shared::cta;\n" ::: "memory"); }
__device__ __forceinline__ void cp_async16(uint32_t dst, const void* src) {
    asm volatile("cp.async.cg.shared.global [%0], [%1], 16;\n" ::"r"(dst), "l"(src) : "memory");
}
__device__ __forceinline__ void cp_async_commit() { asm volatile("cp.async.commit_group;\n" ::: "memory"); }
__device__ __forceinline__ void cp_async_wait_all() { asm volatile("cp.async.wait_group 0;\n" ::: "memory"); }
__device__ __forceinline__ void prefetch_l2(const void* p) { asm volatile("prefetch.global.L2 [%0];\n" ::"l"(p)); }

__device__ __forceinline__ float tanh_approx(float x) {
    float y;
    asm("tanh.approx.f32 %0, %1;" : "=f"(y) : "f"(x));
    return y;
}
__device__ __forceinline__ uint32_t pack_bf16(float lo, float hi) {
    uint32_t r;
    asm("cvt.rn.bf16x2.f32 %0, %1, %2;" : "=r"(r) : "f"(hi), "f"(lo));
    return r;
}
__device__ __forceinline__ float bf_lo(uint32_t v) { return __uint_as_float(v << 16); }
__device__ __forceinline__ float bf_hi(uint32_t v) { return __uint_as_float(v & 0xffff0000u); }

#define ACC32(d)                                                                                             \
    "+f"(d[0]), "+f"(d[1]), "+f"(d[2]), "+f"(d[3]), "+f"(d[4]), "+f"(d[5]), "+f"(d[6]), "+f"(d[7]),          \
        "+f"(d[8]), "+f"(d[9]), "+f"(d[10]), "+f"(d[11]), "+f"(d[12]), "+f"(d[13]), "+f"(d[14]), "+f"(d[15]), \
        "+f"(d[16]), "+f"(d[17]), "+f"(d[18]), "+f"(d[19]), "+f"(d[20]), "+f"(d[21]), "+f"(d[22]),           \
        "+f"(d[23]), "+f"(d[24]), "+f"(d[25]), "+f"(d[26]), "+f"(d[27]), "+f"(d[28]), "+f"(d[29]),           \
        "+f"(d[30]), "+f"(d[31])
#define ACC32_STR                                                                \
    "{%0, %1, %2, %3, %4, %5, %6, %7, %8, %9, %10, %11, %12, %13, %14, %15, "    \
    " %16, %17, %18, %19, %20, %21, %22, %23, %24, %25, %26, %27, %28, %29, %30, %31}"

__device__ __forceinline__ void wgmma_ss_n64_tA(float (&d)[32], uint64_t adesc, uint64_t bdesc, int scale_d) {
    asm volatile(
        "{\n.reg .pred p;\nsetp.ne.b32 p, %34, 0;\n"
        "wgmma.mma_async.sync.aligned.m64n64k16.f32.bf16.bf16 " ACC32_STR ", %32, %33, p, 1, 1, 1, 0;\n}\n"
        : ACC32(d)
        : "l"(adesc), "l"(bdesc), "r"(scale_d));
}
__device__ __forceinline__ void wgmma_ss_n64(float (&d)[32], uint64_t adesc, uint64_t bdesc, int scale_d) {
    asm volatile(
        "{\n.reg .pred p;\nsetp.ne.b32 p, %34, 0;\n"
        "wgmma.mma_async.sync.aligned.m64n64k16.f32.bf16.bf16 " ACC32_STR ", %32, %33, p, 1, 1, 0, 1;\n}\n"
        : ACC32(d)
        : "l"(adesc), "l"(bdesc), "r"(scale_d));
}
__device__ __forceinline__ void wgmma_n96(float (&d)[48], uint32_t a0, uint32_t a1, uint32_t a2, uint32_t a3,
                                          uint64_t bdesc) {
    asm volatile(
        "{\n"
        "wgmma.mma_async.sync.aligned.m64n96k16.f32.bf16.bf16 "
        "{%0, %1, %2, %3, %4, %5, %6, %7, %8, %9, %10, %11, %12, %13, %14, %15, "
        " %16, %17, %18, %19, %20, %21, %22, %23, %24, %25, %26, %27, %28, %29, %30, %31, "
        " %32, %33, %34, %35, %36, %37, %38, %39, %40, %41, %42, %43, %44, %45, %46, %47}, "
        "{%48, %49, %50, %51}, %52, 1, 1, 1, 1;\n"
        "}\n"
        : ACC32(d), "+f"(d[32]), "+f"(d[33]), "+f"(d[34]), "+f"(d[35]), "+f"(d[36]), "+f"(d[37]), "+f"(d[38]),
          "+f"(d[39]), "+f"(d[40]), "+f"(d[41]), "+f"(d[42]), "+f"(d[43]), "+f"(d[44]), "+f"(d[45]), "+f"(d[46]),
          "+f"(d[47])
        : "r"(a0), "r"(a1), "r"(a2), "r"(a3), "l"(bdesc));
}

#define W2_LBO 128
#define W2_SBO (48 * 128)
#define W1_BOX_BYTES (96 * 128)
#define Y_BOX_BYTES (64 * 64)
#define Y_TILE_BYTES (3 * Y_BOX_BYTES)

__device__ __forceinline__ void ln_row4(const uint4 (&xv)[3], const float* __restrict__ s_dwq, uint4 (&y)[3]) {
    float xf[24], dwf[24];
    float s = 0.f;
#pragma unroll
    for (int i = 0; i < 3; i++) {
        uint32_t w[4] = {xv[i].x, xv[i].y, xv[i].z, xv[i].w};
        float4 da = *reinterpret_cast<const float4*>(s_dwq + 32 * i);
        float4 db = *reinterpret_cast<const float4*>(s_dwq + 32 * i + 4);
        dwf[i * 8 + 0] = da.x; dwf[i * 8 + 1] = da.y; dwf[i * 8 + 2] = da.z; dwf[i * 8 + 3] = da.w;
        dwf[i * 8 + 4] = db.x; dwf[i * 8 + 5] = db.y; dwf[i * 8 + 6] = db.z; dwf[i * 8 + 7] = db.w;
#pragma unroll
        for (int p = 0; p < 4; p++) {
            xf[i * 8 + 2 * p] = bf_lo(w[p]);
            xf[i * 8 + 2 * p + 1] = bf_hi(w[p]);
        }
#pragma unroll
        for (int p = 0; p < 8; p++) s = fmaf(xf[i * 8 + p], dwf[i * 8 + p], s);
    }
    s += __shfl_xor_sync(0xffffffffu, s, 1);
    s += __shfl_xor_sync(0xffffffffu, s, 2);
    float nmean = s * (-1.0f / C_IN);
    float v = 0.f;
#pragma unroll
    for (int i = 0; i < 24; i++) {
        xf[i] = fmaf(xf[i], dwf[i], nmean);
        v = fmaf(xf[i], xf[i], v);
    }
    v += __shfl_xor_sync(0xffffffffu, v, 1);
    v += __shfl_xor_sync(0xffffffffu, v, 2);
    float rstd = rsqrtf(v * (1.0f / C_IN) + 1e-5f) * GELU_KAPPA;
#pragma unroll
    for (int i = 0; i < 3; i++) {
        y[i].x = pack_bf16(xf[i * 8 + 0] * rstd, xf[i * 8 + 1] * rstd);
        y[i].y = pack_bf16(xf[i * 8 + 2] * rstd, xf[i * 8 + 3] * rstd);
        y[i].z = pack_bf16(xf[i * 8 + 4] * rstd, xf[i * 8 + 5] * rstd);
        y[i].w = pack_bf16(xf[i * 8 + 6] * rstd, xf[i * 8 + 7] * rstd);
    }
}

__device__ __forceinline__ void ln_tile_inplace(unsigned char* yp, const float* __restrict__ s_dwq) {
    uint4 xv[3], y[3];
#pragma unroll
    for (int i = 0; i < 3; i++) xv[i] = *reinterpret_cast<const uint4*>(yp + i * Y_BOX_BYTES);
    ln_row4(xv, s_dwq, y);
#pragma unroll
    for (int i = 0; i < 3; i++) *reinterpret_cast<uint4*>(yp + i * Y_BOX_BYTES) = y[i];
#pragma unroll
    for (int i = 0; i < 3; i++) xv[i] = *reinterpret_cast<const uint4*>(yp + 512 + i * Y_BOX_BYTES);
    ln_row4(xv, s_dwq, y);
#pragma unroll
    for (int i = 0; i < 3; i++) *reinterpret_cast<uint4*>(yp + 512 + i * Y_BOX_BYTES) = y[i];
}

__device__ __forceinline__ float gelu2(float u) {
    float t = fmaf(u, u, GELU_C0K);
    float a = t * u;
    float th = tanh_approx(a);
    return fmaf(u, th, u);
}

__device__ __forceinline__ void tma_x_tile(uint32_t dst, const CUtensorMap* tmx, uint32_t bar, int tile) {
    mbar_expect_tx(bar, Y_TILE_BYTES);
#pragma unroll
    for (int i = 0; i < 3; i++) tma_load_2d(dst + i * Y_BOX_BYTES, tmx, bar, i * 32, tile * TILE_M);
}

__global__ void __launch_bounds__(NTHR, 1)
k_stats(const __grid_constant__ CUtensorMap tm_x, const __grid_constant__ CUtensorMap tm_w1,
        const __nv_bfloat16* __restrict__ dw, const __nv_bfloat16* __restrict__ w2,
        const __nv_bfloat16* __restrict__ grn_g, const __nv_bfloat16* __restrict__ grn_b) {
    extern __shared__ __align__(1024) unsigned char smem[];
    unsigned char* s_w1 = smem;
    unsigned char* s_y = smem + 73728;
    float* s_dw = reinterpret_cast<float*>(smem + 73728 + NWG * 2 * Y_TILE_BYTES);
    float* s_red = s_dw + 128;
    uint64_t* s_bar = reinterpret_cast<uint64_t*>(s_red + C_H);

    const int tid = threadIdx.x;
    const int wg = tid >> 7;
    const int warp = (tid >> 5) & 3;
    const int lane = tid & 31;
    const int q = lane & 3;
    const int nwg = gridDim.x * NWG;
    int tile = blockIdx.x * NWG + wg;

    if (tid == 0) {
        for (int i = 0; i < 1 + 2 * NWG; i++) mbar_init(smem_u32(s_bar + i), 1);
        asm volatile("fence.mbarrier_init.release.cluster;\n" ::: "memory");
    }
    if (tid < C_IN) s_dw[tid] = __bfloat162float(dw[tid]);
    for (int i = tid; i < C_H; i += NTHR) s_red[i] = 0.f;
    __syncthreads();
    const uint32_t ybuf0 = smem_u32(s_y + wg * 2 * Y_TILE_BYTES);
    const uint32_t bar_y = smem_u32(s_bar + 1 + 2 * wg);
    if (tid == 0) {
        mbar_expect_tx(smem_u32(s_bar), 6 * W1_BOX_BYTES);
        for (int i = 0; i < 6; i++) tma_load_2d(smem_u32(s_w1) + i * W1_BOX_BYTES, &tm_w1, smem_u32(s_bar), i * 64, 0);
    }
    if ((tid & 127) == 0 && tile < NTILES) tma_x_tile(ybuf0, &tm_x, bar_y, tile);

    float ss[12];
#pragma unroll
    for (int i = 0; i < 12; i++) ss[i] = 0.f;

    const uint64_t w1_desc = make_desc(smem_u32(s_w1), W1_BOX_BYTES, 1024, 1);
    const int rl = warp * 16 + (lane >> 2);
    const int yoff = rl * 64 + ((q ^ ((rl >> 1) & 3)) * 16);
    mbar_wait(smem_u32(s_bar), 0);

    int it = 0;
    for (; tile < NTILES; tile += nwg, it++) {
        const int buf = it & 1;
        if ((tid & 127) == 0 && tile + nwg < NTILES) tma_x_tile(ybuf0 + (buf ^ 1) * Y_TILE_BYTES, &tm_x, bar_y + (buf ^ 1) * 8, tile + nwg);
        mbar_wait(bar_y + buf * 8, (it >> 1) & 1);
        unsigned char* ytile = s_y + (wg * 2 + buf) * Y_TILE_BYTES;
        ln_tile_inplace(ytile + yoff, s_dw + 8 * q);
        proxy_fence();
        wg_bar(1 + wg);
        const uint64_t y_desc = make_desc(smem_u32(ytile), 16, 512, 2);
        float S[2][32];
        wg_fence();
#pragma unroll
        for (int t = 0; t < 6; t++)
            wgmma_ss_n64_tA(S[0], w1_desc + ((t * 2048) >> 4), y_desc + (((t >> 1) * Y_BOX_BYTES + (t & 1) * 32) >> 4), t != 0);
        wg_commit();
#pragma unroll
        for (int m = 0; m < 6; m++) {
            if (m + 1 < 6) {
                wg_fence();
#pragma unroll
                for (int t = 0; t < 6; t++)
                    wgmma_ss_n64_tA(S[(m + 1) & 1], w1_desc + (((m + 1) * W1_BOX_BYTES + t * 2048) >> 4),
                                    y_desc + (((t >> 1) * Y_BOX_BYTES + (t & 1) * 32) >> 4), t != 0);
                wg_commit();
                wg_wait<1>();
            } else {
                wg_wait<0>();
            }
            float(&Sc)[32] = S[m & 1];
            float a0 = ss[2 * m], a1 = ss[2 * m + 1];
#pragma unroll
            for (int j = 0; j < 8; j++) {
                float g0 = gelu2(Sc[4 * j]);
                float g1 = gelu2(Sc[4 * j + 1]);
                float g2 = gelu2(Sc[4 * j + 2]);
                float g3 = gelu2(Sc[4 * j + 3]);
                a0 = fmaf(g0, g0, a0);
                a1 = fmaf(g2, g2, a1);
                a0 = fmaf(g1, g1, a0);
                a1 = fmaf(g3, g3, a1);
            }
            ss[2 * m] = a0;
            ss[2 * m + 1] = a1;
        }
        wg_bar(1 + wg);
    }
#pragma unroll
    for (int i = 0; i < 12; i++) {
        float v = ss[i];
        v += __shfl_xor_sync(0xffffffffu, v, 1);
        v += __shfl_xor_sync(0xffffffffu, v, 2);
        if (q == 0) {
            int m = i >> 1, hh = i & 1;
            atomicAdd(&s_red[m * 64 + warp * 16 + hh * 8 + (lane >> 2)], v);
        }
    }
    __syncthreads();
    const float sc = 0.25f / (GELU_KAPPA * GELU_KAPPA);
    for (int i = tid; i < C_H; i += NTHR) atomicAdd(&g_sum[i], s_red[i] * sc);
    __threadfence();
    __syncthreads();
    __shared__ unsigned int s_last;
    if (tid == 0) s_last = (atomicAdd(&g_done, 1u) == gridDim.x - 1);
    __syncthreads();
    if (!s_last) return;
    __threadfence();
    float* s_s = s_red;
    float* s_tmp = s_dw;
    float lsum = 0.f;
    if (tid < C_H) {
        float gx = sqrtf(__ldcg(&g_sum[tid]) + 1e-6f);
        g_sum[tid] = 0.f;
        s_s[tid] = gx;
        lsum = gx;
    }
#pragma unroll
    for (int o = 16; o > 0; o >>= 1) lsum += __shfl_xor_sync(0xffffffffu, lsum, o);
    if (lane == 0) s_tmp[tid >> 5] = lsum;
    if (tid == 0) g_done = 0;
    __syncthreads();
    float tot = 0.f;
#pragma unroll
    for (int i = 0; i < NTHR / 32; i++) tot += s_tmp[i];
    float inv = 1.0f / (tot * (1.0f / C_H) + 1e-6f);
    __syncthreads();
    if (tid < C_H) s_s[tid] = (0.5f / GELU_KAPPA) * (1.0f + __bfloat162float(grn_g[tid]) * (s_s[tid] * inv));
    if (tid < C_IN) s_tmp[tid] = 0.f;
    __syncthreads();
    {
        float a0 = 0.f, a1 = 0.f, a2 = 0.f;
        int kbase = (tid >> 5) * (C_H / (NTHR / 32));
#pragma unroll
        for (int k = kbase; k < kbase + C_H / (NTHR / 32); k++) {
            float b = __bfloat162float(grn_b[k]);
            a0 = fmaf(b, __bfloat162float(w2[k * C_IN + lane]), a0);
            a1 = fmaf(b, __bfloat162float(w2[k * C_IN + lane + 32]), a1);
            a2 = fmaf(b, __bfloat162float(w2[k * C_IN + lane + 64]), a2);
        }
        atomicAdd(&s_tmp[lane], a0);
        atomicAdd(&s_tmp[lane + 32], a1);
        atomicAdd(&s_tmp[lane + 64], a2);
    }
    for (int it2 = tid; it2 < 384 * 12; it2 += NTHR) {
        int kr = it2 & 7;
        int nb = (it2 >> 3) % 12;
        int kb = (it2 >> 3) / 12;
        int k = kb * 8 + kr;
        float sk = s_s[k];
        uint4 v = __ldg(reinterpret_cast<const uint4*>(w2 + k * C_IN + nb * 8));
        uint4 o;
        o.x = pack_bf16(sk * bf_lo(v.x), sk * bf_hi(v.x));
        o.y = pack_bf16(sk * bf_lo(v.y), sk * bf_hi(v.y));
        o.z = pack_bf16(sk * bf_lo(v.z), sk * bf_hi(v.z));
        o.w = pack_bf16(sk * bf_lo(v.w), sk * bf_hi(v.w));
        *reinterpret_cast<uint4*>(g_w2img + nb * W2_SBO + kb * W2_LBO + kr * 16) = o;
    }
    __syncthreads();
    if (tid < C_IN) g_c[tid] = s_tmp[tid];
}

#define NWG2 3
#define NTHR2 (NWG2 * 128)

__device__ __forceinline__ void wgmma_rs_n64(float (&d)[32], uint32_t a0, uint32_t a1, uint32_t a2, uint32_t a3,
                                             uint64_t bdesc, int scale_d) {
    asm volatile(
        "{\n.reg .pred p;\nsetp.ne.b32 p, %37, 0;\n"
        "wgmma.mma_async.sync.aligned.m64n64k16.f32.bf16.bf16 " ACC32_STR ", {%32, %33, %34, %35}, %36, p, 1, 1, 1;\n}\n"
        : ACC32(d)
        : "r"(a0), "r"(a1), "r"(a2), "r"(a3), "l"(bdesc), "r"(scale_d));
}
__device__ __forceinline__ void ldsm_x4(uint32_t addr, uint32_t& r0, uint32_t& r1, uint32_t& r2, uint32_t& r3) {
    asm volatile("ldmatrix.sync.aligned.m8n8.x4.shared.b16 {%0, %1, %2, %3}, [%4];\n"
                 : "=r"(r0), "=r"(r1), "=r"(r2), "=r"(r3) : "r"(addr) : "memory");
}
__device__ __forceinline__ void stsm_x4(uint32_t addr, uint32_t r0, uint32_t r1, uint32_t r2, uint32_t r3) {
    asm volatile("stmatrix.sync.aligned.m8n8.x4.shared.b16 [%0], {%1, %2, %3, %4};\n" ::"r"(addr), "r"(r0), "r"(r1), "r"(r2),
                 "r"(r3) : "memory");
}
__device__ __forceinline__ void tma_store_2d(const CUtensorMap* tm, uint32_t src, int c0, int c1) {
    asm volatile("cp.async.bulk.tensor.2d.global.shared::cta.bulk_group [%0, {%2, %3}], [%1];\n" ::"l"(
                     reinterpret_cast<uint64_t>(tm)), "r"(src), "r"(c0), "r"(c1) : "memory");
}

__device__ __forceinline__ void ln_frag(uint32_t (&f)[6][4], const float* __restrict__ s_dwq) {
    float xa[24], xb[24], dwf[24];
    float sa = 0.f, sb = 0.f;
#pragma unroll
    for (int t = 0; t < 6; t++) {
#pragma unroll
        for (int h = 0; h < 2; h++) {
            float2 d = *reinterpret_cast<const float2*>(s_dwq + 16 * t + 8 * h);
            int i = t * 4 + h * 2;
            dwf[i] = d.x; dwf[i + 1] = d.y;
            xa[i] = bf_lo(f[t][2 * h]); xa[i + 1] = bf_hi(f[t][2 * h]);
            xb[i] = bf_lo(f[t][2 * h + 1]); xb[i + 1] = bf_hi(f[t][2 * h + 1]);
            sa = fmaf(xa[i], d.x, sa); sa = fmaf(xa[i + 1], d.y, sa);
            sb = fmaf(xb[i], d.x, sb); sb = fmaf(xb[i + 1], d.y, sb);
        }
    }
    sa += __shfl_xor_sync(0xffffffffu, sa, 1);
    sb += __shfl_xor_sync(0xffffffffu, sb, 1);
    sa += __shfl_xor_sync(0xffffffffu, sa, 2);
    sb += __shfl_xor_sync(0xffffffffu, sb, 2);
    float ma = sa * (-1.0f / C_IN), mb = sb * (-1.0f / C_IN);
    float va = 0.f, vb = 0.f;
#pragma unroll
    for (int i = 0; i < 24; i++) {
        xa[i] = fmaf(xa[i], dwf[i], ma);
        xb[i] = fmaf(xb[i], dwf[i], mb);
        va = fmaf(xa[i], xa[i], va);
        vb = fmaf(xb[i], xb[i], vb);
    }
    va += __shfl_xor_sync(0xffffffffu, va, 1);
    vb += __shfl_xor_sync(0xffffffffu, vb, 1);
    va += __shfl_xor_sync(0xffffffffu, va, 2);
    vb += __shfl_xor_sync(0xffffffffu, vb, 2);
    float ra = rsqrtf(va * (1.0f / C_IN) + 1e-5f) * GELU_KAPPA;
    float rb = rsqrtf(vb * (1.0f / C_IN) + 1e-5f) * GELU_KAPPA;
#pragma unroll
    for (int t = 0; t < 6; t++) {
#pragma unroll
        for (int h = 0; h < 2; h++) {
            int i = t * 4 + h * 2;
            f[t][2 * h] = pack_bf16(xa[i] * ra, xa[i + 1] * ra);
            f[t][2 * h + 1] = pack_bf16(xb[i] * rb, xb[i + 1] * rb);
        }
    }
}

__global__ void __launch_bounds__(NTHR2, 1)
k_main(const __grid_constant__ CUtensorMap tm_x, const __grid_constant__ CUtensorMap tm_w1,
       const __grid_constant__ CUtensorMap tm_out, const __nv_bfloat16* __restrict__ dw) {
    extern __shared__ __align__(1024) unsigned char smem[];
    unsigned char* s_w1 = smem;
    unsigned char* s_w2 = smem + 73728;
    unsigned char* s_x = smem + 2 * 73728;
    float* s_dw = reinterpret_cast<float*>(smem + 2 * 73728 + NWG2 * 2 * Y_TILE_BYTES);
    float* s_c = s_dw + 128;
    uint64_t* s_bar = reinterpret_cast<uint64_t*>(s_c + 128);

    const int tid = threadIdx.x;
    const int wg = tid >> 7;
    const int warp = (tid >> 5) & 3;
    const int lane = tid & 31;
    const int q = lane & 3;
    const int nwg = gridDim.x * NWG2;
    int tile = blockIdx.x * NWG2 + wg;

    const uint32_t xbuf0 = smem_u32(s_x + wg * 2 * Y_TILE_BYTES);
    const uint32_t bar_x = smem_u32(s_bar + 1 + 2 * wg);
    if (tid == 0) {
        for (int i = 0; i < 1 + 2 * NWG2; i++) mbar_init(smem_u32(s_bar + i), 1);
        asm volatile("fence.mbarrier_init.release.cluster;\n" ::: "memory");
    }
    if (tid < C_IN) { s_dw[tid] = __bfloat162float(dw[tid]); s_c[tid] = g_c[tid]; }
    __syncthreads();
    if (tid == 0) {
        mbar_expect_tx(smem_u32(s_bar), 6 * W1_BOX_BYTES + 73728);
        for (int i = 0; i < 6; i++) tma_load_2d(smem_u32(s_w1) + i * W1_BOX_BYTES, &tm_w1, smem_u32(s_bar), i * 64, 0);
        for (int i = 0; i < 6; i++)
            asm volatile("cp.async.bulk.shared::cluster.global.mbarrier::complete_tx::bytes [%0], [%1], %2, [%3];\n" ::"r"(
                             smem_u32(s_w2) + i * 12288),
                         "l"(g_w2img + i * 12288), "r"(12288), "r"(smem_u32(s_bar))
                         : "memory");
    }
    if ((tid & 127) == 0 && tile < NTILES) tma_x_tile(xbuf0, &tm_x, bar_x, tile);
    mbar_wait(smem_u32(s_bar), 0);

    const uint64_t w1_desc = make_desc(smem_u32(s_w1), W1_BOX_BYTES, 1024, 1);
    const uint64_t w2_desc = make_desc(smem_u32(s_w2), W2_LBO, W2_SBO, 0);
    const int lrow = warp * 16 + ((lane >> 3) & 1) * 8 + (lane & 7);
    const int lhalf = lane >> 4;
    const int lsw = (lrow >> 1) & 3;
    const uint32_t loff0 = lrow * 64 + (((0 + lhalf) ^ lsw) << 4);
    const uint32_t loff1 = lrow * 64 + (((2 + lhalf) ^ lsw) << 4);

    int it = 0;
    for (; tile < NTILES; tile += nwg, it++) {
        const int buf = it & 1;
        const uint32_t xb = xbuf0 + buf * Y_TILE_BYTES;
        if ((tid & 127) == 0 && tile + nwg < NTILES) {
            asm volatile("cp.async.bulk.wait_group.read 0;\n" ::: "memory");
            tma_x_tile(xbuf0 + (buf ^ 1) * Y_TILE_BYTES, &tm_x, bar_x + (buf ^ 1) * 8, tile + nwg);
        }
        mbar_wait(bar_x + buf * 8, (it >> 1) & 1);
        uint32_t f[6][4];
#pragma unroll
        for (int t = 0; t < 6; t++)
            ldsm_x4(xb + (t >> 1) * Y_BOX_BYTES + ((t & 1) ? loff1 : loff0), f[t][0], f[t][1], f[t][2], f[t][3]);
        ln_frag(f, s_dw + 2 * q);

        float O[48];
#pragma unroll
        for (int j = 0; j < 12; j++) {
            float2 cc = *reinterpret_cast<const float2*>(&s_c[8 * j + 2 * q]);
            O[4 * j] = cc.x; O[4 * j + 1] = cc.y; O[4 * j + 2] = cc.x; O[4 * j + 3] = cc.y;
        }
        float S[2][32];
        uint32_t hf[16];
        wg_fence();
#pragma unroll
        for (int t = 0; t < 6; t++) wgmma_rs_n64(S[0], f[t][0], f[t][1], f[t][2], f[t][3], w1_desc + ((t * 2048) >> 4), t != 0);
        wg_commit();
#pragma unroll
        for (int c = 0; c < 6; c++) {
            if (c + 1 < 6) {
                wg_fence();
#pragma unroll
                for (int t = 0; t < 6; t++)
                    wgmma_rs_n64(S[(c + 1) & 1], f[t][0], f[t][1], f[t][2], f[t][3],
                                 w1_desc + (((c + 1) * W1_BOX_BYTES + t * 2048) >> 4), t != 0);
                wg_commit();
                wg_wait<1>();
            } else {
                wg_wait<0>();
            }
            float(&Sc)[32] = S[c & 1];
#pragma unroll
            for (int j = 0; j < 8; j++) {
                float g0 = gelu2(Sc[4 * j]);
                float g1 = gelu2(Sc[4 * j + 1]);
                float g2 = gelu2(Sc[4 * j + 2]);
                float g3 = gelu2(Sc[4 * j + 3]);
                hf[2 * j] = pack_bf16(g0, g1);
                hf[2 * j + 1] = pack_bf16(g2, g3);
            }
            wg_fence();
#pragma unroll
            for (int t = 0; t < 4; t++)
                wgmma_n96(O, hf[4 * t], hf[4 * t + 1], hf[4 * t + 2], hf[4 * t + 3],
                          w2_desc + (((c * 8 + 2 * t) * W2_LBO) >> 4));
            wg_commit();
        }
        uint32_t xr[6][4];
#pragma unroll
        for (int t = 0; t < 6; t++)
            ldsm_x4(xb + (t >> 1) * Y_BOX_BYTES + ((t & 1) ? loff1 : loff0), xr[t][0], xr[t][1], xr[t][2], xr[t][3]);
        wg_wait<0>();
#pragma unroll
        for (int t = 0; t < 6; t++) {
            uint32_t o0 = pack_bf16(bf_lo(xr[t][0]) + O[8 * t + 0], bf_hi(xr[t][0]) + O[8 * t + 1]);
            uint32_t o1 = pack_bf16(bf_lo(xr[t][1]) + O[8 * t + 2], bf_hi(xr[t][1]) + O[8 * t + 3]);
            uint32_t o2 = pack_bf16(bf_lo(xr[t][2]) + O[8 * t + 4], bf_hi(xr[t][2]) + O[8 * t + 5]);
            uint32_t o3 = pack_bf16(bf_lo(xr[t][3]) + O[8 * t + 6], bf_hi(xr[t][3]) + O[8 * t + 7]);
            stsm_x4(xb + (t >> 1) * Y_BOX_BYTES + ((t & 1) ? loff1 : loff0), o0, o1, o2, o3);
        }
        proxy_fence();
        wg_bar(1 + wg);
        if ((tid & 127) == 0) {
#pragma unroll
            for (int i = 0; i < 3; i++) tma_store_2d(&tm_out, xb + i * Y_BOX_BYTES, i * 32, tile * TILE_M);
            asm volatile("cp.async.bulk.commit_group;\n" ::: "memory");
        }
    }
    if ((tid & 127) == 0) asm volatile("cp.async.bulk.wait_group 0;\n" ::: "memory");
}

#define SMEM1 (73728 + NWG * 2 * Y_TILE_BYTES + 512 + 1536 + 128)
#define SMEM2 (2 * 73728 + NWG2 * 2 * Y_TILE_BYTES + 512 + 512 + 64)

typedef CUresult (*PFN_encodeTiled)(CUtensorMap*, CUtensorMapDataType, cuuint32_t, void*, const cuuint64_t*, const cuuint64_t*,
                                    const cuuint32_t*, const cuuint32_t*, CUtensorMapInterleave, CUtensorMapSwizzle,
                                    CUtensorMapL2promotion, CUtensorMapFloatOOBfill);

extern "C" void kernel_launch(void* const* d_in, const int* in_sizes, int n_in, void* d_out, int out_size) {
    const __nv_bfloat16* x = (const __nv_bfloat16*)d_in[0];
    const __nv_bfloat16* dw = (const __nv_bfloat16*)d_in[1];
    const __nv_bfloat16* w1 = (const __nv_bfloat16*)d_in[2];
    const __nv_bfloat16* w2 = (const __nv_bfloat16*)d_in[3];
    const __nv_bfloat16* grn_g = (const __nv_bfloat16*)d_in[4];
    const __nv_bfloat16* grn_b = (const __nv_bfloat16*)d_in[5];

    static int n_sm = 0;
    static CUtensorMap tm_x, tm_w1, tm_out;
    static const void* last_x = nullptr;
    static const void* last_w1 = nullptr;
    static const void* last_out = nullptr;
    static PFN_encodeTiled encode = nullptr;
    if (n_sm == 0) {
        int dev = 0;
        cudaGetDevice(&dev);
        cudaDeviceGetAttribute(&n_sm, cudaDevAttrMultiProcessorCount, dev);
        if (n_sm > MAX_CTAS) n_sm = MAX_CTAS;
        cudaFuncSetAttribute(k_stats, cudaFuncAttributeMaxDynamicSharedMemorySize, SMEM1);
        cudaFuncSetAttribute(k_main, cudaFuncAttributeMaxDynamicSharedMemorySize, SMEM2);
        cudaDriverEntryPointQueryResult qres;
        void* fn = nullptr;
        cudaGetDriverEntryPoint("cuTensorMapEncodeTiled", &fn, cudaEnableDefault, &qres);
        encode = (PFN_encodeTiled)fn;
    }
    if (last_x != x || last_w1 != w1 || last_out != d_out) {
        cuuint64_t dims[2] = {96, (cuuint64_t)NROWS};
        cuuint64_t strides[1] = {192};
        cuuint32_t box[2] = {32, 64};
        cuuint32_t es[2] = {1, 1};
        encode(&tm_x, CU_TENSOR_MAP_DATA_TYPE_BFLOAT16, 2, (void*)x, dims, strides, box, es, CU_TENSOR_MAP_INTERLEAVE_NONE,
               CU_TENSOR_MAP_SWIZZLE_64B, CU_TENSOR_MAP_L2_PROMOTION_L2_128B, CU_TENSOR_MAP_FLOAT_OOB_FILL_NONE);
        encode(&tm_out, CU_TENSOR_MAP_DATA_TYPE_BFLOAT16, 2, d_out, dims, strides, box, es, CU_TENSOR_MAP_INTERLEAVE_NONE,
               CU_TENSOR_MAP_SWIZZLE_64B, CU_TENSOR_MAP_L2_PROMOTION_L2_128B, CU_TENSOR_MAP_FLOAT_OOB_FILL_NONE);
        cuuint64_t dimsw[2] = {384, 96};
        cuuint64_t stridesw[1] = {768};
        cuuint32_t boxw[2] = {64, 96};
        encode(&tm_w1, CU_TENSOR_MAP_DATA_TYPE_BFLOAT16, 2, (void*)w1, dimsw, stridesw, boxw, es, CU_TENSOR_MAP_INTERLEAVE_NONE,
               CU_TENSOR_MAP_SWIZZLE_128B, CU_TENSOR_MAP_L2_PROMOTION_L2_128B, CU_TENSOR_MAP_FLOAT_OOB_FILL_NONE);
        last_x = x;
        last_w1 = w1;
        last_out = d_out;
    }
    k_stats<<<n_sm, NTHR, SMEM1>>>(tm_x, tm_w1, dw, w2, grn_g, grn_b);
    k_main<<<n_sm, NTHR2, SMEM2>>>(tm_x, tm_w1, tm_out, dw);
}
```

```cpp
#include <cuda_runtime.h>
#include <cuda_bf16.h>
#include <stdint.h>
#include <cuda.h>

#define C_IN 96
#define C_H 384
#define NROWS (512 * 512)
#define TILE_M 64
#define NTILES (NROWS / TILE_M)
#define MAX_CTAS 256
#define NWG 4
#define NTHR (NWG * 128)

__device__ float g_sum[C_H];
__device__ unsigned int g_done;
__device__ __align__(1024) unsigned char g_w2img[73728];
__device__ float g_c[C_IN];
#define TSTAMP(i)

#define GELU_KAPPA 0.3292034911525734f
#define GELU_C0K 2.423681954311584f

__device__ __forceinline__ uint32_t smem_u32(const void* p) { return (uint32_t)__cvta_generic_to_shared(p); }
__device__ __forceinline__ uint64_t make_desc(uint32_t addr, uint32_t lbo, uint32_t sbo, uint32_t swz = 0) {
    uint64_t d = 0;
    d |= (uint64_t)((addr & 0x3FFFF) >> 4);
    d |= (uint64_t)((lbo >> 4) & 0x3FFF) << 16;
    d |= (uint64_t)((sbo >> 4) & 0x3FFF) << 32;
    d |= (uint64_t)swz << 62;
    return d;
}
__device__ __forceinline__ void mbar_init(uint32_t bar, uint32_t count) {
    asm volatile("mbarrier.init.shared::cta.b64 [%0], %1;\n" ::"r"(bar), "r"(count) : "memory");
}
__device__ __forceinline__ void mbar_expect_tx(uint32_t bar, uint32_t bytes) {
    asm volatile("mbarrier.arrive.expect_tx.shared::cta.b64 _, [%0], %1;\n" ::"r"(bar), "r"(bytes) : "memory");
}
__device__ __forceinline__ void mbar_wait(uint32_t bar, uint32_t parity) {
    asm volatile(
        "{\n.reg .pred p;\n"
        "WAIT_LOOP:\n"
        "mbarrier.try_wait.parity.shared::cta.b64 p, [%0], %1;\n"
        "@p bra WAIT_DONE;\n"
        "bra WAIT_LOOP;\n"
        "WAIT_DONE:\n}\n" ::"r"(bar), "r"(parity) : "memory");
}
__device__ __forceinline__ void tma_load_2d(uint32_t dst, const CUtensorMap* tm, uint32_t bar, int c0, int c1) {
    asm volatile(
        "cp.async.bulk.tensor.2d.shared::cluster.global.mbarrier::complete_tx::bytes [%0], [%1, {%3, %4}], [%2];\n" ::"r"(dst),
        "l"(reinterpret_cast<uint64_t>(tm)), "r"(bar), "r"(c0), "r"(c1)
        : "memory");
}
__device__ __forceinline__ void wg_fence() { asm volatile("wgmma.fence.sync.aligned;\n" ::: "memory"); }
__device__ __forceinline__ void wg_commit() { asm volatile("wgmma.commit_group.sync.aligned;\n" ::: "memory"); }
template <int N>
__device__ __forceinline__ void wg_wait() { asm volatile("wgmma.wait_group.sync.aligned %0;\n" ::"n"(N) : "memory"); }
__device__ __forceinline__ void wg_bar(int id) { asm volatile("bar.sync %0, 128;" ::"r"(id) : "memory"); }
__device__ __forceinline__ void proxy_fence() {
 asm volatile("fence.proxy.async.shared::cta;\n" ::: "memory"); }
__device__ __forceinline__ void cp_async16(uint32_t dst, const void* src) {
    asm volatile("cp.async.cg.shared.global [%0], [%1], 16;\n" ::"r"(dst), "l"(src) : "memory");
}
__device__ __forceinline__ void cp_async_commit() { asm volatile("cp.async.commit_group;\n" ::: "memory"); }
__device__ __forceinline__ void cp_async_wait_all() { asm volatile("cp.async.wait_group 0;\n" ::: "memory"); }
__device__ __forceinline__ void prefetch_l2(const void* p) { asm volatile("prefetch.global.L2 [%0];\n" ::"l"(p)); }

__device__ __forceinline__ float tanh_approx(float x) {
    float y;
    asm("tanh.approx.f32 %0, %1;" : "=f"(y) : "f"(x));
    return y;
}
__device__ __forceinline__ uint32_t pack_bf16(float lo, float hi) {
    uint32_t r;
    asm("cvt.rn.bf16x2.f32 %0, %1, %2;" : "=r"(r) : "f"(hi), "f"(lo));
    return r;
}
__device__ __forceinline__ float bf_lo(uint32_t v) { return __uint_as_float(v << 16); }
__device__ __forceinline__ float bf_hi(uint32_t v) { return __uint_as_float(v & 0xffff0000u); }

#define ACC32(d)                                                                                             \
    "+f"(d[0]), "+f"(d[1]), "+f"(d[2]), "+f"(d[3]), "+f"(d[4]), "+f"(d[5]), "+f"(d[6]), "+f"(d[7]),          \
        "+f"(d[8]), "+f"(d[9]), "+f"(d[10]), "+f"(d[11]), "+f"(d[12]), "+f"(d[13]), "+f"(d[14]), "+f"(d[15]), \
        "+f"(d[16]), "+f"(d[17]), "+f"(d[18]), "+f"(d[19]), "+f"(d[20]), "+f"(d[21]), "+f"(d[22]),           \
        "+f"(d[23]), "+f"(d[24]), "+f"(d[25]), "+f"(d[26]), "+f"(d[27]), "+f"(d[28]), "+f"(d[29]),           \
        "+f"(d[30]), "+f"(d[31])
#define ACC32_STR                                                                \
    "{%0, %1, %2, %3, %4, %5, %6, %7, %8, %9, %10, %11, %12, %13, %14, %15, "    \
    " %16, %17, %18, %19, %20, %21, %22, %23, %24, %25, %26, %27, %28, %29, %30, %31}"

__device__ __forceinline__ void wgmma_ss_n64_tA(float (&d)[32], uint64_t adesc, uint64_t bdesc, int scale_d) {
    asm volatile(
        "{\n.reg .pred p;\nsetp.ne.b32 p, %34, 0;\n"
        "wgmma.mma_async.sync.aligned.m64n64k16.f32.bf16.bf16 " ACC32_STR ", %32, %33, p, 1, 1, 1, 0;\n}\n"
        : ACC32(d)
        : "l"(adesc), "l"(bdesc), "r"(scale_d));
}
__device__ __forceinline__ void wgmma_ss_n64(float (&d)[32], uint64_t adesc, uint64_t bdesc, int scale_d) {
    asm volatile(
        "{\n.reg .pred p;\nsetp.ne.b32 p, %34, 0;\n"
        "wgmma.mma_async.sync.aligned.m64n64k16.f32.bf16.bf16 " ACC32_STR ", %32, %33, p, 1, 1, 0, 1;\n}\n"
        : ACC32(d)
        : "l"(adesc), "l"(bdesc), "r"(scale_d));
}
__device__ __forceinline__ void wgmma_n96(float (&d)[48], uint32_t a0, uint32_t a1, uint32_t a2, uint32_t a3,
                                          uint64_t bdesc) {
    asm volatile(
        "{\n"
        "wgmma.mma_async.sync.aligned.m64n96k16.f32.bf16.bf16 "
        "{%0, %1, %2, %3, %4, %5, %6, %7, %8, %9, %10, %11, %12, %13, %14, %15, "
        " %16, %17, %18, %19, %20, %21, %22, %23, %24, %25, %26, %27, %28, %29, %30, %31, "
        " %32, %33, %34, %35, %36, %37, %38, %39, %40, %41, %42, %43, %44, %45, %46, %47}, "
        "{%48, %49, %50, %51}, %52, 1, 1, 1, 1;\n"
        "}\n"
        : ACC32(d), "+f"(d[32]), "+f"(d[33]), "+f"(d[34]), "+f"(d[35]), "+f"(d[36]), "+f"(d[37]), "+f"(d[38]),
          "+f"(d[39]), "+f"(d[40]), "+f"(d[41]), "+f"(d[42]), "+f"(d[43]), "+f"(d[44]), "+f"(d[45]), "+f"(d[46]),
          "+f"(d[47])
        : "r"(a0), "r"(a1), "r"(a2), "r"(a3), "l"(bdesc));
}

#define W2_LBO 128
#define W2_SBO (48 * 128)
#define W1_BOX_BYTES (96 * 128)
#define Y_BOX_BYTES (64 * 64)
#define Y_TILE_BYTES (3 * Y_BOX_BYTES)

__device__ __forceinline__ void ln_row4(const uint4 (&xv)[3], const float* __restrict__ s_dwq, uint4 (&y)[3]) {
    float xf[24], dwf[24];
    float s = 0.f;
#pragma unroll
    for (int i = 0; i < 3; i++) {
        uint32_t w[4] = {xv[i].x, xv[i].y, xv[i].z, xv[i].w};
        float4 da = *reinterpret_cast<const float4*>(s_dwq + 32 * i);
        float4 db = *reinterpret_cast<const float4*>(s_dwq + 32 * i + 4);
        dwf[i * 8 + 0] = da.x; dwf[i * 8 + 1] = da.y; dwf[i * 8 + 2] = da.z; dwf[i * 8 + 3] = da.w;
        dwf[i * 8 + 4] = db.x; dwf[i * 8 + 5] = db.y; dwf[i * 8 + 6] = db.z; dwf[i * 8 + 7] = db.w;
#pragma unroll
        for (int p = 0; p < 4; p++) {
            xf[i * 8 + 2 * p] = bf_lo(w[p]);
            xf[i * 8 + 2 * p + 1] = bf_hi(w[p]);
        }
#pragma unroll
        for (int p = 0; p < 8; p++) s = fmaf(xf[i * 8 + p], dwf[i * 8 + p], s);
    }
    s += __shfl_xor_sync(0xffffffffu, s, 1);
    s += __shfl_xor_sync(0xffffffffu, s, 2);
    float nmean = s * (-1.0f / C_IN);
    float v = 0.f;
#pragma unroll
    for (int i = 0; i < 24; i++) {
        xf[i] = fmaf(xf[i], dwf[i], nmean);
        v = fmaf(xf[i], xf[i], v);
    }
    v += __shfl_xor_sync(0xffffffffu, v, 1);
    v += __shfl_xor_sync(0xffffffffu, v, 2);
    float rstd = rsqrtf(v * (1.0f / C_IN) + 1e-5f) * GELU_KAPPA;
#pragma unroll
    for (int i = 0; i < 3; i++) {
        y[i].x = pack_bf16(xf[i * 8 + 0] * rstd, xf[i * 8 + 1] * rstd);
        y[i].y = pack_bf16(xf[i * 8 + 2] * rstd, xf[i * 8 + 3] * rstd);
        y[i].z = pack_bf16(xf[i * 8 + 4] * rstd, xf[i * 8 + 5] * rstd);
        y[i].w = pack_bf16(xf[i * 8 + 6] * rstd, xf[i * 8 + 7] * rstd);
    }
}

__device__ __forceinline__ void ln_tile_inplace(unsigned char* yp, const float* __restrict__ s_dwq) {
    uint4 xv[3], y[3];
#pragma unroll
    for (int i = 0; i < 3; i++) xv[i] = *reinterpret_cast<const uint4*>(yp + i * Y_BOX_BYTES);
    ln_row4(xv, s_dwq, y);
#pragma unroll
    for (int i = 0; i < 3; i++) *reinterpret_cast<uint4*>(yp + i * Y_BOX_BYTES) = y[i];
#pragma unroll
    for (int i = 0; i < 3; i++) xv[i] = *reinterpret_cast<const uint4*>(yp + 512 + i * Y_BOX_BYTES);
    ln_row4(xv, s_dwq, y);
#pragma unroll
    for (int i = 0; i < 3; i++) *reinterpret_cast<uint4*>(yp + 512 + i * Y_BOX_BYTES) = y[i];
}

__device__ __forceinline__ float gelu2(float u) {
    float t = fmaf(u, u, GELU_C0K);
    float a = t * u;
    float th = tanh_approx(a);
    return fmaf(u, th, u);
}

__device__ __forceinline__ void tma_x_tile(uint32_t dst, const CUtensorMap* tmx, uint32_t bar, int tile) {
    mbar_expect_tx(bar, Y_TILE_BYTES);
#pragma unroll
    for (int i = 0; i < 3; i++) tma_load_2d(dst + i * Y_BOX_BYTES, tmx, bar, i * 32, tile * TILE_M);
}

__global__ void __launch_bounds__(NTHR, 1)
k_stats(const __grid_constant__ CUtensorMap tm_x, const __grid_constant__ CUtensorMap tm_w1,
        const __nv_bfloat16* __restrict__ dw, const __nv_bfloat16* __restrict__ w2,
        const __nv_bfloat16* __restrict__ grn_g, const __nv_bfloat16* __restrict__ grn_b) {
    extern __shared__ __align__(1024) unsigned char smem[];
    unsigned char* s_w1 = smem;
    unsigned char* s_y = smem + 73728;
    float* s_dw = reinterpret_cast<float*>(smem + 73728 + NWG * 2 * Y_TILE_BYTES);
    float* s_red = s_dw + 128;
    uint64_t* s_bar = reinterpret_cast<uint64_t*>(s_red + C_H);

    const int tid = threadIdx.x;
    const int wg = tid >> 7;
    const int warp = (tid >> 5) & 3;
    const int lane = tid & 31;
    const int q = lane & 3;
    const int nwg = gridDim.x * NWG;
    int tile = blockIdx.x * NWG + wg;

    if (tid == 0) {
        for (int i = 0; i < 1 + 2 * NWG; i++) mbar_init(smem_u32(s_bar + i), 1);
        asm volatile("fence.mbarrier_init.release.cluster;\n" ::: "memory");
    }
    if (tid < C_IN) s_dw[tid] = __bfloat162float(dw[tid]);
    for (int i = tid; i < C_H; i += NTHR) s_red[i] = 0.f;
    __syncthreads();
    const uint32_t ybuf0 = smem_u32(s_y + wg * 2 * Y_TILE_BYTES);
    const uint32_t bar_y = smem_u32(s_bar + 1 + 2 * wg);
    if (tid == 0) {
        mbar_expect_tx(smem_u32(s_bar), 6 * W1_BOX_BYTES);
        for (int i = 0; i < 6; i++) tma_load_2d(smem_u32(s_w1) + i * W1_BOX_BYTES, &tm_w1, smem_u32(s_bar), i * 64, 0);
    }
    if ((tid & 127) == 0 && tile < NTILES) tma_x_tile(ybuf0, &tm_x, bar_y, tile);

    float ss[12];
#pragma unroll
    for (int i = 0; i < 12; i++) ss[i] = 0.f;

    const uint64_t w1_desc = make_desc(smem_u32(s_w1), W1_BOX_BYTES, 1024, 1);
    const int rl = warp * 16 + (lane >> 2);
    const int yoff = rl * 64 + ((q ^ ((rl >> 1) & 3)) * 16);
    mbar_wait(smem_u32(s_bar), 0);

    int it = 0;
    for (; tile < NTILES; tile += nwg, it++) {
        const int buf = it & 1;
        if ((tid & 127) == 0 && tile + nwg < NTILES) tma_x_tile(ybuf0 + (buf ^ 1) * Y_TILE_BYTES, &tm_x, bar_y + (buf ^ 1) * 8, tile + nwg);
        mbar_wait(bar_y + buf * 8, (it >> 1) & 1);
        unsigned char* ytile = s_y + (wg * 2 + buf) * Y_TILE_BYTES;
        ln_tile_inplace(ytile + yoff, s_dw + 8 * q);
        proxy_fence();
        wg_bar(1 + wg);
        const uint64_t y_desc = make_desc(smem_u32(ytile), 16, 512, 2);
        float S[2][32];
        wg_fence();
#pragma unroll
        for (int t = 0; t < 6; t++)
            wgmma_ss_n64_tA(S[0], w1_desc + ((t * 2048) >> 4), y_desc + (((t >> 1) * Y_BOX_BYTES + (t & 1) * 32) >> 4), t != 0);
        wg_commit();
#pragma unroll
        for (int m = 0; m < 6; m++) {
            if (m + 1 < 6) {
                wg_fence();
#pragma unroll
                for (int t = 0; t < 6; t++)
                    wgmma_ss_n64_tA(S[(m + 1) & 1], w1_desc + (((m + 1) * W1_BOX_BYTES + t * 2048) >> 4),
                                    y_desc + (((t >> 1) * Y_BOX_BYTES + (t & 1) * 32) >> 4), t != 0);
                wg_commit();
                wg_wait<1>();
            } else {
                wg_wait<0>();
            }
            float(&Sc)[32] = S[m & 1];
            float a0 = ss[2 * m], a1 = ss[2 * m + 1];
#pragma unroll
            for (int j = 0; j < 8; j++) {
                float g0 = gelu2(Sc[4 * j]);
                float g1 = gelu2(Sc[4 * j + 1]);
                float g2 = gelu2(Sc[4 * j + 2]);
                float g3 = gelu2(Sc[4 * j + 3]);
                a0 = fmaf(g0, g0, a0);
                a1 = fmaf(g2, g2, a1);
                a0 = fmaf(g1, g1, a0);
                a1 = fmaf(g3, g3, a1);
            }
            ss[2 * m] = a0;
            ss[2 * m + 1] = a1;
        }
        wg_bar(1 + wg);
    }
#pragma unroll
    for (int i = 0; i < 12; i++) {
        float v = ss[i];
        v += __shfl_xor_sync(0xffffffffu, v, 1);
        v += __shfl_xor_sync(0xffffffffu, v, 2);
        if (q == 0) {
            int m = i >> 1, hh = i & 1;
            atomicAdd(&s_red[m * 64 + warp * 16 + hh * 8 + (lane >> 2)], v);
        }
    }
    __syncthreads();
    const float sc = 0.25f / (GELU_KAPPA * GELU_KAPPA);
    for (int i = tid; i < C_H; i += NTHR) atomicAdd(&g_sum[i], s_red[i] * sc);
    __threadfence();
    __syncthreads();
    __shared__ unsigned int s_last;
    if (tid == 0) s_last = (atomicAdd(&g_done, 1u) == gridDim.x - 1);
    __syncthreads();
    if (!s_last) return;
    __threadfence();
    float* s_s = s_red;
    float* s_tmp = s_dw;
    float lsum = 0.f;
    if (tid < C_H) {
        float gx = sqrtf(__ldcg(&g_sum[tid]) + 1e-6f);
        g_sum[tid] = 0.f;
        s_s[tid] = gx;
        lsum = gx;
    }
#pragma unroll
    for (int o = 16; o > 0; o >>= 1) lsum += __shfl_xor_sync(0xffffffffu, lsum, o);
    if (lane == 0) s_tmp[tid >> 5] = lsum;
    if (tid == 0) g_done = 0;
    __syncthreads();
    float tot = 0.f;
#pragma unroll
    for (int i = 0; i < NTHR / 32; i++) tot += s_tmp[i];
    float inv = 1.0f / (tot * (1.0f / C_H) + 1e-6f);
    __syncthreads();
    if (tid < C_H) s_s[tid] = (0.5f / GELU_KAPPA) * (1.0f + __bfloat162float(grn_g[tid]) * (s_s[tid] * inv));
    if (tid < C_IN) s_tmp[tid] = 0.f;
    __syncthreads();
    {
        float a0 = 0.f, a1 = 0.f, a2 = 0.f;
        int kbase = (tid >> 5) * (C_H / (NTHR / 32));
#pragma unroll
        for (int k = kbase; k < kbase + C_H / (NTHR / 32); k++) {
            float b = __bfloat162float(grn_b[k]);
            a0 = fmaf(b, __bfloat162float(w2[k * C_IN + lane]), a0);
            a1 = fmaf(b, __bfloat162float(w2[k * C_IN + lane + 32]), a1);
            a2 = fmaf(b, __bfloat162float(w2[k * C_IN + lane + 64]), a2);
        }
        atomicAdd(&s_tmp[lane], a0);
        atomicAdd(&s_tmp[lane + 32], a1);
        atomicAdd(&s_tmp[lane + 64], a2);
    }
    for (int it2 = tid; it2 < 384 * 12; it2 += NTHR) {
        int kr = it2 & 7;
        int nb = (it2 >> 3) % 12;
        int kb = (it2 >> 3) / 12;
        int k = kb * 8 + kr;
        float sk = s_s[k];
        uint4 v = __ldg(reinterpret_cast<const uint4*>(w2 + k * C_IN + nb * 8));
        uint4 o;
        o.x = pack_bf16(sk * bf_lo(v.x), sk * bf_hi(v.x));
        o.y = pack_bf16(sk * bf_lo(v.y), sk * bf_hi(v.y));
        o.z = pack_bf16(sk * bf_lo(v.z), sk * bf_hi(v.z));
        o.w = pack_bf16(sk * bf_lo(v.w), sk * bf_hi(v.w));
        *reinterpret_cast<uint4*>(g_w2img + nb * W2_SBO + kb * W2_LBO + kr * 16) = o;
    }
    __syncthreads();
    if (tid < C_IN) g_c[tid] = s_tmp[tid];
}

#define NWG2 3
#define NTHR2 (NWG2 * 128)

__device__ __forceinline__ void wgmma_rs_n64(float (&d)[32], uint32_t a0, uint32_t a1, uint32_t a2, uint32_t a3,
                                             uint64_t bdesc, int scale_d) {
    asm volatile(
        "{\n.reg .pred p;\nsetp.ne.b32 p, %37, 0;\n"
        "wgmma.mma_async.sync.aligned.m64n64k16.f32.bf16.bf16 " ACC32_STR ", {%32, %33, %34, %35}, %36, p, 1, 1, 1;\n}\n"
        : ACC32(d)
        : "r"(a0), "r"(a1), "r"(a2), "r"(a3), "l"(bdesc), "r"(scale_d));
}
__device__ __forceinline__ void ldsm_x4(uint32_t addr, uint32_t& r0, uint32_t& r1, uint32_t& r2, uint32_t& r3) {
    asm volatile("ldmatrix.sync.aligned.m8n8.x4.shared.b16 {%0, %1, %2, %3}, [%4];\n"
                 : "=r"(r0), "=r"(r1), "=r"(r2), "=r"(r3) : "r"(addr) : "memory");
}
__device__ __forceinline__ void stsm_x4(uint32_t addr, uint32_t r0, uint32_t r1, uint32_t r2, uint32_t r3) {
    asm volatile("stmatrix.sync.aligned.m8n8.x4.shared.b16 [%0], {%1, %2, %3, %4};\n" ::"r"(addr), "r"(r0), "r"(r1), "r"(r2),
                 "r"(r3) : "memory");
}
__device__ __forceinline__ void tma_store_2d(const CUtensorMap* tm, uint32_t src, int c0, int c1) {
    asm volatile("cp.async.bulk.tensor.2d.global.shared::cta.bulk_group [%0, {%2, %3}], [%1];\n" ::"l"(
                     reinterpret_cast<uint64_t>(tm)), "r"(src), "r"(c0), "r"(c1) : "memory");
}

__device__ __forceinline__ void ln_frag(uint32_t (&f)[6][4], const float* __restrict__ s_dwq) {
    float xa[24], xb[24], dwf[24];
    float sa = 0.f, sb = 0.f;
#pragma unroll
    for (int t = 0; t < 6; t++) {
#pragma unroll
        for (int h = 0; h < 2; h++) {
            float2 d = *reinterpret_cast<const float2*>(s_dwq + 16 * t + 8 * h);
            int i = t * 4 + h * 2;
            dwf[i] = d.x; dwf[i + 1] = d.y;
            xa[i] = bf_lo(f[t][2 * h]); xa[i + 1] = bf_hi(f[t][2 * h]);
            xb[i] = bf_lo(f[t][2 * h + 1]); xb[i + 1] = bf_hi(f[t][2 * h + 1]);
            sa = fmaf(xa[i], d.x, sa); sa = fmaf(xa[i + 1], d.y, sa);
            sb = fmaf(xb[i], d.x, sb); sb = fmaf(xb[i + 1], d.y, sb);
        }
    }
    sa += __shfl_xor_sync(0xffffffffu, sa, 1);
    sb += __shfl_xor_sync(0xffffffffu, sb, 1);
    sa += __shfl_xor_sync(0xffffffffu, sa, 2);
    sb += __shfl_xor_sync(0xffffffffu, sb, 2);
    float ma = sa * (-1.0f / C_IN), mb = sb * (-1.0f / C_IN);
    float va = 0.f, vb = 0.f;
#pragma unroll
    for (int i = 0; i < 24; i++) {
        xa[i] = fmaf(xa[i], dwf[i], ma);
        xb[i] = fmaf(xb[i], dwf[i], mb);
        va = fmaf(xa[i], xa[i], va);
        vb = fmaf(xb[i], xb[i], vb);
    }
    va += __shfl_xor_sync(0xffffffffu, va, 1);
    vb += __shfl_xor_sync(0xffffffffu, vb, 1);
    va += __shfl_xor_sync(0xffffffffu, va, 2);
    vb += __shfl_xor_sync(0xffffffffu, vb, 2);
    float ra = rsqrtf(va * (1.0f / C_IN) + 1e-5f) * GELU_KAPPA;
    float rb = rsqrtf(vb * (1.0f / C_IN) + 1e-5f) * GELU_KAPPA;
#pragma unroll
    for (int t = 0; t < 6; t++) {
#pragma unroll
        for (int h = 0; h < 2; h++) {
            int i = t * 4 + h * 2;
            f[t][2 * h] = pack_bf16(xa[i] * ra, xa[i + 1] * ra);
            f[t][2 * h + 1] = pack_bf16(xb[i] * rb, xb[i + 1] * rb);
        }
    }
}

__global__ void __launch_bounds__(NTHR2, 1)
k_main(const __grid_constant__ CUtensorMap tm_x, const __grid_constant__ CUtensorMap tm_w1,
       const __grid_constant__ CUtensorMap tm_out, const __nv_bfloat16* __restrict__ dw) {
    extern __shared__ __align__(1024) unsigned char smem[];
    unsigned char* s_w1 = smem;
    unsigned char* s_w2 = smem + 73728;
    unsigned char* s_x = smem + 2 * 73728;
    float* s_dw = reinterpret_cast<float*>(smem + 2 * 73728 + NWG2 * 2 * Y_TILE_BYTES);
    float* s_c = s_dw + 128;
    uint64_t* s_bar = reinterpret_cast<uint64_t*>(s_c + 128);

    const int tid = threadIdx.x;
    const int wg = tid >> 7;
    const int warp = (tid >> 5) & 3;
    const int lane = tid & 31;
    const int q = lane & 3;
    const int nwg = gridDim.x * NWG2;
    int tile = blockIdx.x * NWG2 + wg;

    const uint32_t xbuf0 = smem_u32(s_x + wg * 2 * Y_TILE_BYTES);
    const uint32_t bar_x = smem_u32(s_bar + 1 + 2 * wg);
    if (tid == 0) {
        for (int i = 0; i < 1 + 2 * NWG2; i++) mbar_init(smem_u32(s_bar + i), 1);
        asm volatile("fence.mbarrier_init.release.cluster;\n" ::: "memory");
    }
    if (tid < C_IN) { s_dw[tid] = __bfloat162float(dw[tid]); s_c[tid] = g_c[tid]; }
    __syncthreads();
    if (tid == 0) {
        mbar_expect_tx(smem_u32(s_bar), 6 * W1_BOX_BYTES + 73728);
        for (int i = 0; i < 6; i++) tma_load_2d(smem_u32(s_w1) + i * W1_BOX_BYTES, &tm_w1, smem_u32(s_bar), i * 64, 0);
        for (int i = 0; i < 6; i++)
            asm volatile("cp.async.bulk.shared::cluster.global.mbarrier::complete_tx::bytes [%0], [%1], %2, [%3];\n" ::"r"(
                             smem_u32(s_w2) + i * 12288),
                         "l"(g_w2img + i * 12288), "r"(12288), "r"(smem_u32(s_bar))
                         : "memory");
    }
    if ((tid & 127) == 0 && tile < NTILES) tma_x_tile(xbuf0, &tm_x, bar_x, tile);
    mbar_wait(smem_u32(s_bar), 0);

    const uint64_t w1_desc = make_desc(smem_u32(s_w1), W1_BOX_BYTES, 1024, 1);
    const uint64_t w2_desc = make_desc(smem_u32(s_w2), W2_LBO, W2_SBO, 0);
    const int lrow = warp * 16 + ((lane >> 3) & 1) * 8 + (lane & 7);
    const int lhalf = lane >> 4;
    const int lsw = (lrow >> 1) & 3;
    const uint32_t loff0 = lrow * 64 + (((0 + lhalf) ^ lsw) << 4);
    const uint32_t loff1 = lrow * 64 + (((2 + lhalf) ^ lsw) << 4);

    int it = 0;
    for (; tile < NTILES; tile += nwg, it++) {
        const int buf = it & 1;
        const uint32_t xb = xbuf0 + buf * Y_TILE_BYTES;
        if ((tid & 127) == 0 && tile + nwg < NTILES) {
            asm volatile("cp.async.bulk.wait_group.read 0;\n" ::: "memory");
            tma_x_tile(xbuf0 + (buf ^ 1) * Y_TILE_BYTES, &tm_x, bar_x + (buf ^ 1) * 8, tile + nwg);
        }
        mbar_wait(bar_x + buf * 8, (it >> 1) & 1);
        uint32_t f[6][4];
#pragma unroll
        for (int t = 0; t < 6; t++)
            ldsm_x4(xb + (t >> 1) * Y_BOX_BYTES + ((t & 1) ? loff1 : loff0), f[t][0], f[t][1], f[t][2], f[t][3]);
        ln_frag(f, s_dw + 2 * q);

        float O[48];
#pragma unroll
        for (int j = 0; j < 12; j++) {
            float2 cc = *reinterpret_cast<const float2*>(&s_c[8 * j + 2 * q]);
            O[4 * j] = cc.x; O[4 * j + 1] = cc.y; O[4 * j + 2] = cc.x; O[4 * j + 3] = cc.y;
        }
        float S[32];
        uint32_t hf[16];
        wg_fence();
#pragma unroll
        for (int t = 0; t < 6; t++) wgmma_rs_n64(S, f[t][0], f[t][1], f[t][2], f[t][3], w1_desc + ((t * 2048) >> 4), t != 0);
        wg_commit();
#pragma unroll
        for (int c = 0; c < 6; c++) {
            wg_wait<0>();
#pragma unroll
            for (int j = 0; j < 8; j++) {
                float g0 = gelu2(S[4 * j]);
                float g1 = gelu2(S[4 * j + 1]);
                float g2 = gelu2(S[4 * j + 2]);
                float g3 = gelu2(S[4 * j + 3]);
                hf[2 * j] = pack_bf16(g0, g1);
                hf[2 * j + 1] = pack_bf16(g2, g3);
            }
            wg_fence();
#pragma unroll
            for (int t = 0; t < 4; t++)
                wgmma_n96(O, hf[4 * t], hf[4 * t + 1], hf[4 * t + 2], hf[4 * t + 3],
                          w2_desc + (((c * 8 + 2 * t) * W2_LBO) >> 4));
            if (c + 1 < 6) {
#pragma unroll
                for (int t = 0; t < 6; t++)
                    wgmma_rs_n64(S, f[t][0], f[t][1], f[t][2], f[t][3],
                                 w1_desc + (((c + 1) * W1_BOX_BYTES + t * 2048) >> 4), t != 0);
            }
            wg_commit();
        }
        uint32_t xr[6][4];
#pragma unroll
        for (int t = 0; t < 6; t++)
            ldsm_x4(xb + (t >> 1) * Y_BOX_BYTES + ((t & 1) ? loff1 : loff0), xr[t][0], xr[t][1], xr[t][2], xr[t][3]);
        wg_wait<0>();
#pragma unroll
        for (int t = 0; t < 6; t++) {
            uint32_t o0 = pack_bf16(bf_lo(xr[t][0]) + O[8 * t + 0], bf_hi(xr[t][0]) + O[8 * t + 1]);
            uint32_t o1 = pack_bf16(bf_lo(xr[t][1]) + O[8 * t + 2], bf_hi(xr[t][1]) + O[8 * t + 3]);
            uint32_t o2 = pack_bf16(bf_lo(xr[t][2]) + O[8 * t + 4], bf_hi(xr[t][2]) + O[8 * t + 5]);
            uint32_t o3 = pack_bf16(bf_lo(xr[t][3]) + O[8 * t + 6], bf_hi(xr[t][3]) + O[8 * t + 7]);
            stsm_x4(xb + (t >> 1) * Y_BOX_BYTES + ((t & 1) ? loff1 : loff0), o0, o1, o2, o3);
        }
        proxy_fence();
        wg_bar(1 + wg);
        if ((tid & 127) == 0) {
#pragma unroll
            for (int i = 0; i < 3; i++) tma_store_2d(&tm_out, xb + i * Y_BOX_BYTES, i * 32, tile * TILE_M);
            asm volatile("cp.async.bulk.commit_group;\n" ::: "memory");
        }
    }
    if ((tid & 127) == 0) asm volatile("cp.async.bulk.wait_group 0;\n" ::: "memory");
}

#define SMEM1 (73728 + NWG * 2 * Y_TILE_BYTES + 512 + 1536 + 128)
#define SMEM2 (2 * 73728 + NWG2 * 2 * Y_TILE_BYTES + 512 + 512 + 64)

typedef CUresult (*PFN_encodeTiled)(CUtensorMap*, CUtensorMapDataType, cuuint32_t, void*, const cuuint64_t*, const cuuint64_t*,
                                    const cuuint32_t*, const cuuint32_t*, CUtensorMapInterleave, CUtensorMapSwizzle,
                                    CUtensorMapL2promotion, CUtensorMapFloatOOBfill);

extern "C" void kernel_launch(void* const* d_in, const int* in_sizes, int n_in, void* d_out, int out_size) {
    const __nv_bfloat16* x = (const __nv_bfloat16*)d_in[0];
    const __nv_bfloat16* dw = (const __nv_bfloat16*)d_in[1];
    const __nv_bfloat16* w1 = (const __nv_bfloat16*)d_in[2];
    const __nv_bfloat16* w2 = (const __nv_bfloat16*)d_in[3];
    const __nv_bfloat16* grn_g = (const __nv_bfloat16*)d_in[4];
    const __nv_bfloat16* grn_b = (const __nv_bfloat16*)d_in[5];

    static int n_sm = 0;
    static CUtensorMap tm_x, tm_w1, tm_out;
    static const void* last_x = nullptr;
    static const void* last_w1 = nullptr;
    static const void* last_out = nullptr;
    static PFN_encodeTiled encode = nullptr;
    if (n_sm == 0) {
        int dev = 0;
        cudaGetDevice(&dev);
        cudaDeviceGetAttribute(&n_sm, cudaDevAttrMultiProcessorCount, dev);
        if (n_sm > MAX_CTAS) n_sm = MAX_CTAS;
        cudaFuncSetAttribute(k_stats, cudaFuncAttributeMaxDynamicSharedMemorySize, SMEM1);
        cudaFuncSetAttribute(k_main, cudaFuncAttributeMaxDynamicSharedMemorySize, SMEM2);
        cudaDriverEntryPointQueryResult qres;
        void* fn = nullptr;
        cudaGetDriverEntryPoint("cuTensorMapEncodeTiled", &fn, cudaEnableDefault, &qres);
        encode = (PFN_encodeTiled)fn;
    }
    if (last_x != x || last_w1 != w1 || last_out != d_out) {
        cuuint64_t dims[2] = {96, (cuuint64_t)NROWS};
        cuuint64_t strides[1] = {192};
        cuuint32_t box[2] = {32, 64};
        cuuint32_t es[2] = {1, 1};
        encode(&tm_x, CU_TENSOR_MAP_DATA_TYPE_BFLOAT16, 2, (void*)x, dims, strides, box, es, CU_TENSOR_MAP_INTERLEAVE_NONE,
               CU_TENSOR_MAP_SWIZZLE_64B, CU_TENSOR_MAP_L2_PROMOTION_L2_128B, CU_TENSOR_MAP_FLOAT_OOB_FILL_NONE);
        encode(&tm_out, CU_TENSOR_MAP_DATA_TYPE_BFLOAT16, 2, d_out, dims, strides, box, es, CU_TENSOR_MAP_INTERLEAVE_NONE,
               CU_TENSOR_MAP_SWIZZLE_64B, CU_TENSOR_MAP_L2_PROMOTION_L2_128B, CU_TENSOR_MAP_FLOAT_OOB_FILL_NONE);
        cuuint64_t dimsw[2] = {384, 96};
        cuuint64_t stridesw[1] = {768};
        cuuint32_t boxw[2] = {64, 96};
        encode(&tm_w1, CU_TENSOR_MAP_DATA_TYPE_BFLOAT16, 2, (void*)w1, dimsw, stridesw, boxw, es, CU_TENSOR_MAP_INTERLEAVE_NONE,
               CU_TENSOR_MAP_SWIZZLE_128B, CU_TENSOR_MAP_L2_PROMOTION_L2_128B, CU_TENSOR_MAP_FLOAT_OOB_FILL_NONE);
        last_x = x;
        last_w1 = w1;
        last_out = d_out;
    }
    k_stats<<<n_sm, NTHR, SMEM1>>>(tm_x, tm_w1, dw, w2, grn_g, grn_b);
    k_main<<<n_sm, NTHR2, SMEM2>>>(tm_x, tm_w1, tm_out, dw);
}
```

```cpp
#include <cuda_runtime.h>
#include <cuda_bf16.h>
#include <stdint.h>
#include <cuda.h>

#define C_IN 96
#define C_H 384
#define NROWS (512 * 512)
#define TILE_M 64
#define NTILES (NROWS / TILE_M)
#define MAX_CTAS 256
#define NWG 4
#define NTHR (NWG * 128)

__device__ float g_sum[C_H];
__device__ unsigned int g_done;
__device__ __align__(1024) unsigned char g_w2img[73728];
__device__ float g_c[C_IN];
#define TSTAMP(i)

#define GELU_KAPPA 0.3292034911525734f
#define GELU_C0K 2.423681954311584f

__device__ __forceinline__ uint32_t smem_u32(const void* p) { return (uint32_t)__cvta_generic_to_shared(p); }
__device__ __forceinline__ uint64_t make_desc(uint32_t addr, uint32_t lbo, uint32_t sbo, uint32_t swz = 0) {
    uint64_t d = 0;
    d |= (uint64_t)((addr & 0x3FFFF) >> 4);
    d |= (uint64_t)((lbo >> 4) & 0x3FFF) << 16;
    d |= (uint64_t)((sbo >> 4) & 0x3FFF) << 32;
    d |= (uint64_t)swz << 62;
    return d;
}
__device__ __forceinline__ void mbar_init(uint32_t bar, uint32_t count) {
    asm volatile("mbarrier.init.shared::cta.b64 [%0], %1;\n" ::"r"(bar), "r"(count) : "memory");
}
__device__ __forceinline__ void mbar_expect_tx(uint32_t bar, uint32_t bytes) {
    asm volatile("mbarrier.arrive.expect_tx.shared::cta.b64 _, [%0], %1;\n" ::"r"(bar), "r"(bytes) : "memory");
}
__device__ __forceinline__ void mbar_wait(uint32_t bar, uint32_t parity) {
    asm volatile(
        "{\n.reg .pred p;\n"
        "WAIT_LOOP:\n"
        "mbarrier.try_wait.parity.shared::cta.b64 p, [%0], %1;\n"
        "@p bra WAIT_DONE;\n"
        "bra WAIT_LOOP;\n"
        "WAIT_DONE:\n}\n" ::"r"(bar), "r"(parity) : "memory");
}
__device__ __forceinline__ void tma_load_2d(uint32_t dst, const CUtensorMap* tm, uint32_t bar, int c0, int c1) {
    asm volatile(
        "cp.async.bulk.tensor.2d.shared::cluster.global.mbarrier::complete_tx::bytes [%0], [%1, {%3, %4}], [%2];\n" ::"r"(dst),
        "l"(reinterpret_cast<uint64_t>(tm)), "r"(bar), "r"(c0), "r"(c1)
        : "memory");
}
__device__ __forceinline__ void wg_fence() { asm volatile("wgmma.fence.sync.aligned;\n" ::: "memory"); }
__device__ __forceinline__ void wg_commit() { asm volatile("wgmma.commit_group.sync.aligned;\n" ::: "memory"); }
template <int N>
__device__ __forceinline__ void wg_wait() { asm volatile("wgmma.wait_group.sync.aligned %0;\n" ::"n"(N) : "memory"); }
__device__ __forceinline__ void wg_bar(int id) { asm volatile("bar.sync %0, 128;" ::"r"(id) : "memory"); }
__device__ __forceinline__ void proxy_fence() {
 asm volatile("fence.proxy.async.shared::cta;\n" ::: "memory"); }
__device__ __forceinline__ void cp_async16(uint32_t dst, const void* src) {
    asm volatile("cp.async.cg.shared.global [%0], [%1], 16;\n" ::"r"(dst), "l"(src) : "memory");
}
__device__ __forceinline__ void cp_async_commit() { asm volatile("cp.async.commit_group;\n" ::: "memory"); }
__device__ __forceinline__ void cp_async_wait_all() { asm volatile("cp.async.wait_group 0;\n" ::: "memory"); }
__device__ __forceinline__ void prefetch_l2(const void* p) { asm volatile("prefetch.global.L2 [%0];\n" ::"l"(p)); }

__device__ __forceinline__ float tanh_approx(float x) {
    float y;
    asm("tanh.approx.f32 %0, %1;" : "=f"(y) : "f"(x));
    return y;
}
__device__ __forceinline__ uint32_t pack_bf16(float lo, float hi) {
    uint32_t r;
    asm("cvt.rn.bf16x2.f32 %0, %1, %2;" : "=r"(r) : "f"(hi), "f"(lo));
    return r;
}
__device__ __forceinline__ float bf_lo(uint32_t v) { return __uint_as_float(v << 16); }
__device__ __forceinline__ float bf_hi(uint32_t v) { return __uint_as_float(v & 0xffff0000u); }

#define ACC32(d)                                                                                             \
    "+f"(d[0]), "+f"(d[1]), "+f"(d[2]), "+f"(d[3]), "+f"(d[4]), "+f"(d[5]), "+f"(d[6]), "+f"(d[7]),          \
        "+f"(d[8]), "+f"(d[9]), "+f"(d[10]), "+f"(d[11]), "+f"(d[12]), "+f"(d[13]), "+f"(d[14]), "+f"(d[15]), \
        "+f"(d[16]), "+f"(d[17]), "+f"(d[18]), "+f"(d[19]), "+f"(d[20]), "+f"(d[21]), "+f"(d[22]),           \
        "+f"(d[23]), "+f"(d[24]), "+f"(d[25]), "+f"(d[26]), "+f"(d[27]), "+f"(d[28]), "+f"(d[29]),           \
        "+f"(d[30]), "+f"(d[31])
#define ACC32_STR                                                                \
    "{%0, %1, %2, %3, %4, %5, %6, %7, %8, %9, %10, %11, %12, %13, %14, %15, "    \
    " %16, %17, %18, %19, %20, %21, %22, %23, %24, %25, %26, %27, %28, %29, %30, %31}"

__device__ __forceinline__ void wgmma_ss_n64_tA(float (&d)[32], uint64_t adesc, uint64_t bdesc, int scale_d) {
    asm volatile(
        "{\n.reg .pred p;\nsetp.ne.b32 p, %34, 0;\n"
        "wgmma.mma_async.sync.aligned.m64n64k16.f32.bf16.bf16 " ACC32_STR ", %32, %33, p, 1, 1, 1, 0;\n}\n"
        : ACC32(d)
        : "l"(adesc), "l"(bdesc), "r"(scale_d));
}
__device__ __forceinline__ void wgmma_ss_n64(float (&d)[32], uint64_t adesc, uint64_t bdesc, int scale_d) {
    asm volatile(
        "{\n.reg .pred p;\nsetp.ne.b32 p, %34, 0;\n"
        "wgmma.mma_async.sync.aligned.m64n64k16.f32.bf16.bf16 " ACC32_STR ", %32, %33, p, 1, 1, 0, 1;\n}\n"
        : ACC32(d)
        : "l"(adesc), "l"(bdesc), "r"(scale_d));
}
__device__ __forceinline__ void wgmma_n96(float (&d)[48], uint32_t a0, uint32_t a1, uint32_t a2, uint32_t a3,
                                          uint64_t bdesc) {
    asm volatile(
        "{\n"
        "wgmma.mma_async.sync.aligned.m64n96k16.f32.bf16.bf16 "
        "{%0, %1, %2, %3, %4, %5, %6, %7, %8, %9, %10, %11, %12, %13, %14, %15, "
        " %16, %17, %18, %19, %20, %21, %22, %23, %24, %25, %26, %27, %28, %29, %30, %31, "
        " %32, %33, %34, %35, %36, %37, %38, %39, %40, %41, %42, %43, %44, %45, %46, %47}, "
        "{%48, %49, %50, %51}, %52, 1, 1, 1, 1;\n"
        "}\n"
        : ACC32(d), "+f"(d[32]), "+f"(d[33]), "+f"(d[34]), "+f"(d[35]), "+f"(d[36]), "+f"(d[37]), "+f"(d[38]),
          "+f"(d[39]), "+f"(d[40]), "+f"(d[41]), "+f"(d[42]), "+f"(d[43]), "+f"(d[44]), "+f"(d[45]), "+f"(d[46]),
          "+f"(d[47])
        : "r"(a0), "r"(a1), "r"(a2), "r"(a3), "l"(bdesc));
}

#define W2_LBO 128
#define W2_SBO (48 * 128)
#define W1_BOX_BYTES (96 * 128)
#define Y_BOX_BYTES (64 * 64)
#define Y_TILE_BYTES (3 * Y_BOX_BYTES)

__device__ __forceinline__ void ln_row4(const uint4 (&xv)[3], const float* __restrict__ s_dwq, uint4 (&y)[3]) {
    float xf[24], dwf[24];
    float s = 0.f;
#pragma unroll
    for (int i = 0; i < 3; i++) {
        uint32_t w[4] = {xv[i].x, xv[i].y, xv[i].z, xv[i].w};
        float4 da = *reinterpret_cast<const float4*>(s_dwq + 32 * i);
        float4 db = *reinterpret_cast<const float4*>(s_dwq + 32 * i + 4);
        dwf[i * 8 + 0] = da.x; dwf[i * 8 + 1] = da.y; dwf[i * 8 + 2] = da.z; dwf[i * 8 + 3] = da.w;
        dwf[i * 8 + 4] = db.x; dwf[i * 8 + 5] = db.y; dwf[i * 8 + 6] = db.z; dwf[i * 8 + 7] = db.w;
#pragma unroll
        for (int p = 0; p < 4; p++) {
            xf[i * 8 + 2 * p] = bf_lo(w[p]);
            xf[i * 8 + 2 * p + 1] = bf_hi(w[p]);
        }
#pragma unroll
        for (int p = 0; p < 8; p++) s = fmaf(xf[i * 8 + p], dwf[i * 8 + p], s);
    }
    s += __shfl_xor_sync(0xffffffffu, s, 1);
    s += __shfl_xor_sync(0xffffffffu, s, 2);
    float nmean = s * (-1.0f / C_IN);
    float v = 0.f;
#pragma unroll
    for (int i = 0; i < 24; i++) {
        xf[i] = fmaf(xf[i], dwf[i], nmean);
        v = fmaf(xf[i], xf[i], v);
    }
    v += __shfl_xor_sync(0xffffffffu, v, 1);
    v += __shfl_xor_sync(0xffffffffu, v, 2);
    float rstd = rsqrtf(v * (1.0f / C_IN) + 1e-5f) * GELU_KAPPA;
#pragma unroll
    for (int i = 0; i < 3; i++) {
        y[i].x = pack_bf16(xf[i * 8 + 0] * rstd, xf[i * 8 + 1] * rstd);
        y[i].y = pack_bf16(xf[i * 8 + 2] * rstd, xf[i * 8 + 3] * rstd);
        y[i].z = pack_bf16(xf[i * 8 + 4] * rstd, xf[i * 8 + 5] * rstd);
        y[i].w = pack_bf16(xf[i * 8 + 6] * rstd, xf[i * 8 + 7] * rstd);
    }
}

__device__ __forceinline__ void ln_tile_inplace(unsigned char* yp, const float* __restrict__ s_dwq) {
    uint4 xv[3], y[3];
#pragma unroll
    for (int i = 0; i < 3; i++) xv[i] = *reinterpret_cast<const uint4*>(yp + i * Y_BOX_BYTES);
    ln_row4(xv, s_dwq, y);
#pragma unroll
    for (int i = 0; i < 3; i++) *reinterpret_cast<uint4*>(yp + i * Y_BOX_BYTES) = y[i];
#pragma unroll
    for (int i = 0; i < 3; i++) xv[i] = *reinterpret_cast<const uint4*>(yp + 512 + i * Y_BOX_BYTES);
    ln_row4(xv, s_dwq, y);
#pragma unroll
    for (int i = 0; i < 3; i++) *reinterpret_cast<uint4*>(yp + 512 + i * Y_BOX_BYTES) = y[i];
}

__device__ __forceinline__ float gelu2(float u) {
    float t = fmaf(u, u, GELU_C0K);
    float a = t * u;
    float th = tanh_approx(a);
    return fmaf(u, th, u);
}

__device__ __forceinline__ void tma_x_tile(uint32_t dst, const CUtensorMap* tmx, uint32_t bar, int tile) {
    mbar_expect_tx(bar, Y_TILE_BYTES);
#pragma unroll
    for (int i = 0; i < 3; i++) tma_load_2d(dst + i * Y_BOX_BYTES, tmx, bar, i * 32, tile * TILE_M);
}

__global__ void __launch_bounds__(NTHR, 1)
k_stats(const __grid_constant__ CUtensorMap tm_x, const __grid_constant__ CUtensorMap tm_w1,
        const __nv_bfloat16* __restrict__ dw, const __nv_bfloat16* __restrict__ w2,
        const __nv_bfloat16* __restrict__ grn_g, const __nv_bfloat16* __restrict__ grn_b) {
    extern __shared__ __align__(1024) unsigned char smem[];
    unsigned char* s_w1 = smem;
    unsigned char* s_y = smem + 73728;
    float* s_dw = reinterpret_cast<float*>(smem + 73728 + NWG * 2 * Y_TILE_BYTES);
    float* s_red = s_dw + 128;
    uint64_t* s_bar = reinterpret_cast<uint64_t*>(s_red + C_H);

    const int tid = threadIdx.x;
    const int wg = tid >> 7;
    const int warp = (tid >> 5) & 3;
    const int lane = tid & 31;
    const int q = lane & 3;
    const int nwg = gridDim.x * NWG;
    int tile = blockIdx.x * NWG + wg;

    if (tid == 0) {
        for (int i = 0; i < 1 + 2 * NWG; i++) mbar_init(smem_u32(s_bar + i), 1);
        asm volatile("fence.mbarrier_init.release.cluster;\n" ::: "memory");
    }
    if (tid < C_IN) s_dw[tid] = __bfloat162float(dw[tid]);
    for (int i = tid; i < C_H; i += NTHR) s_red[i] = 0.f;
    __syncthreads();
    const uint32_t ybuf0 = smem_u32(s_y + wg * 2 * Y_TILE_BYTES);
    const uint32_t bar_y = smem_u32(s_bar + 1 + 2 * wg);
    if (tid == 0) {
        mbar_expect_tx(smem_u32(s_bar), 6 * W1_BOX_BYTES);
        for (int i = 0; i < 6; i++) tma_load_2d(smem_u32(s_w1) + i * W1_BOX_BYTES, &tm_w1, smem_u32(s_bar), i * 64, 0);
    }
    if ((tid & 127) == 0 && tile < NTILES) tma_x_tile(ybuf0, &tm_x, bar_y, tile);

    float ss[12];
#pragma unroll
    for (int i = 0; i < 12; i++) ss[i] = 0.f;

    const uint64_t w1_desc = make_desc(smem_u32(s_w1), W1_BOX_BYTES, 1024, 1);
    const int rl = warp * 16 + (lane >> 2);
    const int yoff = rl * 64 + ((q ^ ((rl >> 1) & 3)) * 16);
    mbar_wait(smem_u32(s_bar), 0);

    int it = 0;
    for (; tile < NTILES; tile += nwg, it++) {
        const int buf = it & 1;
        if ((tid & 127) == 0 && tile + nwg < NTILES) tma_x_tile(ybuf0 + (buf ^ 1) * Y_TILE_BYTES, &tm_x, bar_y + (buf ^ 1) * 8, tile + nwg);
        mbar_wait(bar_y + buf * 8, (it >> 1) & 1);
        unsigned char* ytile = s_y + (wg * 2 + buf) * Y_TILE_BYTES;
        ln_tile_inplace(ytile + yoff, s_dw + 8 * q);
        proxy_fence();
        wg_bar(1 + wg);
        const uint64_t y_desc = make_desc(smem_u32(ytile), 16, 512, 2);
        float S[2][32];
        wg_fence();
#pragma unroll
        for (int t = 0; t < 6; t++)
            wgmma_ss_n64_tA(S[0], w1_desc + ((t * 2048) >> 4), y_desc + (((t >> 1) * Y_BOX_BYTES + (t & 1) * 32) >> 4), t != 0);
        wg_commit();
#pragma unroll
        for (int m = 0; m < 6; m++) {
            if (m + 1 < 6) {
                wg_fence();
#pragma unroll
                for (int t = 0; t < 6; t++)
                    wgmma_ss_n64_tA(S[(m + 1) & 1], w1_desc + (((m + 1) * W1_BOX_BYTES + t * 2048) >> 4),
                                    y_desc + (((t >> 1) * Y_BOX_BYTES + (t & 1) * 32) >> 4), t != 0);
                wg_commit();
                wg_wait<1>();
            } else {
                wg_wait<0>();
            }
            float(&Sc)[32] = S[m & 1];
            float a0 = ss[2 * m], a1 = ss[2 * m + 1];
#pragma unroll
            for (int j = 0; j < 8; j++) {
                float g0 = gelu2(Sc[4 * j]);
                float g1 = gelu2(Sc[4 * j + 1]);
                float g2 = gelu2(Sc[4 * j + 2]);
                float g3 = gelu2(Sc[4 * j + 3]);
                a0 = fmaf(g0, g0, a0);
                a1 = fmaf(g2, g2, a1);
                a0 = fmaf(g1, g1, a0);
                a1 = fmaf(g3, g3, a1);
            }
            ss[2 * m] = a0;
            ss[2 * m + 1] = a1;
        }
        wg_bar(1 + wg);
    }
#pragma unroll
    for (int i = 0; i < 12; i++) {
        float v = ss[i];
        v += __shfl_xor_sync(0xffffffffu, v, 1);
        v += __shfl_xor_sync(0xffffffffu, v, 2);
        if (q == 0) {
            int m = i >> 1, hh = i & 1;
            atomicAdd(&s_red[m * 64 + warp * 16 + hh * 8 + (lane >> 2)], v);
        }
    }
    __syncthreads();
    const float sc = 0.25f / (GELU_KAPPA * GELU_KAPPA);
    for (int i = tid; i < C_H; i += NTHR) atomicAdd(&g_sum[i], s_red[i] * sc);
    __threadfence();
    __syncthreads();
    __shared__ unsigned int s_last;
    if (tid == 0) s_last = (atomicAdd(&g_done, 1u) == gridDim.x - 1);
    __syncthreads();
    if (!s_last) return;
    __threadfence();
    float* s_s = s_red;
    float* s_tmp = s_dw;
    float lsum = 0.f;
    if (tid < C_H) {
        float gx = sqrtf(__ldcg(&g_sum[tid]) + 1e-6f);
        g_sum[tid] = 0.f;
        s_s[tid] = gx;
        lsum = gx;
    }
#pragma unroll
    for (int o = 16; o > 0; o >>= 1) lsum += __shfl_xor_sync(0xffffffffu, lsum, o);
    if (lane == 0) s_tmp[tid >> 5] = lsum;
    if (tid == 0) g_done = 0;
    __syncthreads();
    float tot = 0.f;
#pragma unroll
    for (int i = 0; i < NTHR / 32; i++) tot += s_tmp[i];
    float inv = 1.0f / (tot * (1.0f / C_H) + 1e-6f);
    __syncthreads();
    if (tid < C_H) s_s[tid] = (0.5f / GELU_KAPPA) * (1.0f + __bfloat162float(grn_g[tid]) * (s_s[tid] * inv));
    if (tid < C_IN) s_tmp[tid] = 0.f;
    __syncthreads();
    {
        float a0 = 0.f, a1 = 0.f, a2 = 0.f;
        int kbase = (tid >> 5) * (C_H / (NTHR / 32));
#pragma unroll
        for (int k = kbase; k < kbase + C_H / (NTHR / 32); k++) {
            float b = __bfloat162float(grn_b[k]);
            a0 = fmaf(b, __bfloat162float(w2[k * C_IN + lane]), a0);
            a1 = fmaf(b, __bfloat162float(w2[k * C_IN + lane + 32]), a1);
            a2 = fmaf(b, __bfloat162float(w2[k * C_IN + lane + 64]), a2);
        }
        atomicAdd(&s_tmp[lane], a0);
        atomicAdd(&s_tmp[lane + 32], a1);
        atomicAdd(&s_tmp[lane + 64], a2);
    }
    for (int it2 = tid; it2 < 384 * 12; it2 += NTHR) {
        int kr = it2 & 7;
        int nb = (it2 >> 3) % 12;
        int kb = (it2 >> 3) / 12;
        int k = kb * 8 + kr;
        float sk = s_s[k];
        uint4 v = __ldg(reinterpret_cast<const uint4*>(w2 + k * C_IN + nb * 8));
        uint4 o;
        o.x = pack_bf16(sk * bf_lo(v.x), sk * bf_hi(v.x));
        o.y = pack_bf16(sk * bf_lo(v.y), sk * bf_hi(v.y));
        o.z = pack_bf16(sk * bf_lo(v.z), sk * bf_hi(v.z));
        o.w = pack_bf16(sk * bf_lo(v.w), sk * bf_hi(v.w));
        *reinterpret_cast<uint4*>(g_w2img + nb * W2_SBO + kb * W2_LBO + kr * 16) = o;
    }
    __syncthreads();
    if (tid < C_IN) g_c[tid] = s_tmp[tid];
}

#define NWG2 2
#define NTHR2 (NWG2 * 128)

__device__ __forceinline__ void wgmma_rs_n64(float (&d)[32], uint32_t a0, uint32_t a1, uint32_t a2, uint32_t a3,
                                             uint64_t bdesc, int scale_d) {
    asm volatile(
        "{\n.reg .pred p;\nsetp.ne.b32 p, %37, 0;\n"
        "wgmma.mma_async.sync.aligned.m64n64k16.f32.bf16.bf16 " ACC32_STR ", {%32, %33, %34, %35}, %36, p, 1, 1, 1;\n}\n"
        : ACC32(d)
        : "r"(a0), "r"(a1), "r"(a2), "r"(a3), "l"(bdesc), "r"(scale_d));
}
__device__ __forceinline__ void ldsm_x4(uint32_t addr, uint32_t& r0, uint32_t& r1, uint32_t& r2, uint32_t& r3) {
    asm volatile("ldmatrix.sync.aligned.m8n8.x4.shared.b16 {%0, %1, %2, %3}, [%4];\n"
                 : "=r"(r0), "=r"(r1), "=r"(r2), "=r"(r3) : "r"(addr) : "memory");
}
__device__ __forceinline__ void stsm_x4(uint32_t addr, uint32_t r0, uint32_t r1, uint32_t r2, uint32_t r3) {
    asm volatile("stmatrix.sync.aligned.m8n8.x4.shared.b16 [%0], {%1, %2, %3, %4};\n" ::"r"(addr), "r"(r0), "r"(r1), "r"(r2),
                 "r"(r3) : "memory");
}
__device__ __forceinline__ void tma_store_2d(const CUtensorMap* tm, uint32_t src, int c0, int c1) {
    asm volatile("cp.async.bulk.tensor.2d.global.shared::cta.bulk_group [%0, {%2, %3}], [%1];\n" ::"l"(
                     reinterpret_cast<uint64_t>(tm)), "r"(src), "r"(c0), "r"(c1) : "memory");
}

__device__ __forceinline__ void ln_frag(uint32_t (&f)[6][4], const float* __restrict__ s_dwq) {
    float xa[24], xb[24], dwf[24];
    float sa = 0.f, sb = 0.f;
#pragma unroll
    for (int t = 0; t < 6; t++) {
#pragma unroll
        for (int h = 0; h < 2; h++) {
            float2 d = *reinterpret_cast<const float2*>(s_dwq + 16 * t + 8 * h);
            int i = t * 4 + h * 2;
            dwf[i] = d.x; dwf[i + 1] = d.y;
            xa[i] = bf_lo(f[t][2 * h]); xa[i + 1] = bf_hi(f[t][2 * h]);
            xb[i] = bf_lo(f[t][2 * h + 1]); xb[i + 1] = bf_hi(f[t][2 * h + 1]);
            sa = fmaf(xa[i], d.x, sa); sa = fmaf(xa[i + 1], d.y, sa);
            sb = fmaf(xb[i], d.x, sb); sb = fmaf(xb[i + 1], d.y, sb);
        }
    }
    sa += __shfl_xor_sync(0xffffffffu, sa, 1);
    sb += __shfl_xor_sync(0xffffffffu, sb, 1);
    sa += __shfl_xor_sync(0xffffffffu, sa, 2);
    sb += __shfl_xor_sync(0xffffffffu, sb, 2);
    float ma = sa * (-1.0f / C_IN), mb = sb * (-1.0f / C_IN);
    float va = 0.f, vb = 0.f;
#pragma unroll
    for (int i = 0; i < 24; i++) {
        xa[i] = fmaf(xa[i], dwf[i], ma);
        xb[i] = fmaf(xb[i], dwf[i], mb);
        va = fmaf(xa[i], xa[i], va);
        vb = fmaf(xb[i], xb[i], vb);
    }
    va += __shfl_xor_sync(0xffffffffu, va, 1);
    vb += __shfl_xor_sync(0xffffffffu, vb, 1);
    va += __shfl_xor_sync(0xffffffffu, va, 2);
    vb += __shfl_xor_sync(0xffffffffu, vb, 2);
    float ra = rsqrtf(va * (1.0f / C_IN) + 1e-5f) * GELU_KAPPA;
    float rb = rsqrtf(vb * (1.0f / C_IN) + 1e-5f) * GELU_KAPPA;
#pragma unroll
    for (int t = 0; t < 6; t++) {
#pragma unroll
        for (int h = 0; h < 2; h++) {
            int i = t * 4 + h * 2;
            f[t][2 * h] = pack_bf16(xa[i] * ra, xa[i + 1] * ra);
            f[t][2 * h + 1] = pack_bf16(xb[i] * rb, xb[i + 1] * rb);
        }
    }
}

__global__ void __launch_bounds__(NTHR2, 1)
k_main(const __grid_constant__ CUtensorMap tm_x, const __grid_constant__ CUtensorMap tm_w1,
       const __grid_constant__ CUtensorMap tm_out, const __nv_bfloat16* __restrict__ dw) {
    extern __shared__ __align__(1024) unsigned char smem[];
    unsigned char* s_w1 = smem;
    unsigned char* s_w2 = smem + 73728;
    unsigned char* s_x = smem + 2 * 73728;
    float* s_dw = reinterpret_cast<float*>(smem + 2 * 73728 + NWG2 * 2 * Y_TILE_BYTES);
    float* s_c = s_dw + 128;
    uint64_t* s_bar = reinterpret_cast<uint64_t*>(s_c + 128);

    const int tid = threadIdx.x;
    const int wg = tid >> 7;
    const int warp = (tid >> 5) & 3;
    const int lane = tid & 31;
    const int q = lane & 3;
    const int nwg = gridDim.x * NWG2;
    int tile = blockIdx.x * NWG2 + wg;

    const uint32_t xbuf0 = smem_u32(s_x + wg * 2 * Y_TILE_BYTES);
    const uint32_t bar_x = smem_u32(s_bar + 1 + 2 * wg);
    if (tid == 0) {
        for (int i = 0; i < 1 + 2 * NWG2; i++) mbar_init(smem_u32(s_bar + i), 1);
        asm volatile("fence.mbarrier_init.release.cluster;\n" ::: "memory");
    }
    if (tid < C_IN) { s_dw[tid] = __bfloat162float(dw[tid]); s_c[tid] = g_c[tid]; }
    __syncthreads();
    if (tid == 0) {
        mbar_expect_tx(smem_u32(s_bar), 6 * W1_BOX_BYTES + 73728);
        for (int i = 0; i < 6; i++) tma_load_2d(smem_u32(s_w1) + i * W1_BOX_BYTES, &tm_w1, smem_u32(s_bar), i * 64, 0);
        for (int i = 0; i < 6; i++)
            asm volatile("cp.async.bulk.shared::cluster.global.mbarrier::complete_tx::bytes [%0], [%1], %2, [%3];\n" ::"r"(
                             smem_u32(s_w2) + i * 12288),
                         "l"(g_w2img + i * 12288), "r"(12288), "r"(smem_u32(s_bar))
                         : "memory");
    }
    if ((tid & 127) == 0 && tile < NTILES) tma_x_tile(xbuf0, &tm_x, bar_x, tile);
    mbar_wait(smem_u32(s_bar), 0);

    const uint64_t w1_desc = make_desc(smem_u32(s_w1), W1_BOX_BYTES, 1024, 1);
    const uint64_t w2_desc = make_desc(smem_u32(s_w2), W2_LBO, W2_SBO, 0);
    const int lrow = warp * 16 + ((lane >> 3) & 1) * 8 + (lane & 7);
    const int lhalf = lane >> 4;
    const int lsw = (lrow >> 1) & 3;
    const uint32_t loff0 = lrow * 64 + (((0 + lhalf) ^ lsw) << 4);
    const uint32_t loff1 = lrow * 64 + (((2 + lhalf) ^ lsw) << 4);

    int it = 0;
    for (; tile < NTILES; tile += nwg, it++) {
        const int buf = it & 1;
        const uint32_t xb = xbuf0 + buf * Y_TILE_BYTES;
        if ((tid & 127) == 0 && tile + nwg < NTILES) {
            asm volatile("cp.async.bulk.wait_group.read 0;\n" ::: "memory");
            tma_x_tile(xbuf0 + (buf ^ 1) * Y_TILE_BYTES, &tm_x, bar_x + (buf ^ 1) * 8, tile + nwg);
        }
        mbar_wait(bar_x + buf * 8, (it >> 1) & 1);
        uint32_t f[6][4];
#pragma unroll
        for (int t = 0; t < 6; t++)
            ldsm_x4(xb + (t >> 1) * Y_BOX_BYTES + ((t & 1) ? loff1 : loff0), f[t][0], f[t][1], f[t][2], f[t][3]);
        ln_frag(f, s_dw + 2 * q);

        float O[48];
#pragma unroll
        for (int j = 0; j < 12; j++) {
            float2 cc = *reinterpret_cast<const float2*>(&s_c[8 * j + 2 * q]);
            O[4 * j] = cc.x; O[4 * j + 1] = cc.y; O[4 * j + 2] = cc.x; O[4 * j + 3] = cc.y;
        }
        float S[2][32];
        uint32_t hf[2][16];
        wg_fence();
#pragma unroll
        for (int t = 0; t < 6; t++) wgmma_rs_n64(S[0], f[t][0], f[t][1], f[t][2], f[t][3], w1_desc + ((t * 2048) >> 4), t != 0);
        wg_commit();
#pragma unroll
        for (int c = 0; c < 6; c++) {
            if (c + 1 < 6) {
                wg_fence();
#pragma unroll
                for (int t = 0; t < 6; t++)
                    wgmma_rs_n64(S[(c + 1) & 1], f[t][0], f[t][1], f[t][2], f[t][3],
                                 w1_desc + (((c + 1) * W1_BOX_BYTES + t * 2048) >> 4), t != 0);
                wg_commit();
                if (c == 0) wg_wait<1>(); else wg_wait<2>();
            } else {
                wg_wait<1>();
            }
            float(&Sc)[32] = S[c & 1];
            uint32_t(&h)[16] = hf[c & 1];
#pragma unroll
            for (int j = 0; j < 8; j++) {
                float g0 = gelu2(Sc[4 * j]);
                float g1 = gelu2(Sc[4 * j + 1]);
                float g2 = gelu2(Sc[4 * j + 2]);
                float g3 = gelu2(Sc[4 * j + 3]);
                h[2 * j] = pack_bf16(g0, g1);
                h[2 * j + 1] = pack_bf16(g2, g3);
            }
            wg_fence();
#pragma unroll
            for (int t = 0; t < 4; t++)
                wgmma_n96(O, h[4 * t], h[4 * t + 1], h[4 * t + 2], h[4 * t + 3],
                          w2_desc + (((c * 8 + 2 * t) * W2_LBO) >> 4));
            wg_commit();
        }
        uint32_t xr[6][4];
#pragma unroll
        for (int t = 0; t < 6; t++)
            ldsm_x4(xb + (t >> 1) * Y_BOX_BYTES + ((t & 1) ? loff1 : loff0), xr[t][0], xr[t][1], xr[t][2], xr[t][3]);
        wg_wait<0>();
#pragma unroll
        for (int t = 0; t < 6; t++) {
            uint32_t o0 = pack_bf16(bf_lo(xr[t][0]) + O[8 * t + 0], bf_hi(xr[t][0]) + O[8 * t + 1]);
            uint32_t o1 = pack_bf16(bf_lo(xr[t][1]) + O[8 * t + 2], bf_hi(xr[t][1]) + O[8 * t + 3]);
            uint32_t o2 = pack_bf16(bf_lo(xr[t][2]) + O[8 * t + 4], bf_hi(xr[t][2]) + O[8 * t + 5]);
            uint32_t o3 = pack_bf16(bf_lo(xr[t][3]) + O[8 * t + 6], bf_hi(xr[t][3]) + O[8 * t + 7]);
            stsm_x4(xb + (t >> 1) * Y_BOX_BYTES + ((t & 1) ? loff1 : loff0), o0, o1, o2, o3);
        }
        proxy_fence();
        wg_bar(1 + wg);
        if ((tid & 127) == 0) {
#pragma unroll
            for (int i = 0; i < 3; i++) tma_store_2d(&tm_out, xb + i * Y_BOX_BYTES, i * 32, tile * TILE_M);
            asm volatile("cp.async.bulk.commit_group;\n" ::: "memory");
        }
    }
    if ((tid & 127) == 0) asm volatile("cp.async.bulk.wait_group 0;\n" ::: "memory");
}

#define SMEM1 (73728 + NWG * 2 * Y_TILE_BYTES + 512 + 1536 + 128)
#define SMEM2 (2 * 73728 + NWG2 * 2 * Y_TILE_BYTES + 512 + 512 + 64)

typedef CUresult (*PFN_encodeTiled)(CUtensorMap*, CUtensorMapDataType, cuuint32_t, void*, const cuuint64_t*, const cuuint64_t*,
                                    const cuuint32_t*, const cuuint32_t*, CUtensorMapInterleave, CUtensorMapSwizzle,
                                    CUtensorMapL2promotion, CUtensorMapFloatOOBfill);

extern "C" void kernel_launch(void* const* d_in, const int* in_sizes, int n_in, void* d_out, int out_size) {
    const __nv_bfloat16* x = (const __nv_bfloat16*)d_in[0];
    const __nv_bfloat16* dw = (const __nv_bfloat16*)d_in[1];
    const __nv_bfloat16* w1 = (const __nv_bfloat16*)d_in[2];
    const __nv_bfloat16* w2 = (const __nv_bfloat16*)d_in[3];
    const __nv_bfloat16* grn_g = (const __nv_bfloat16*)d_in[4];
    const __nv_bfloat16* grn_b = (const __nv_bfloat16*)d_in[5];

    static int n_sm = 0;
    static CUtensorMap tm_x, tm_w1, tm_out;
    static const void* last_x = nullptr;
    static const void* last_w1 = nullptr;
    static const void* last_out = nullptr;
    static PFN_encodeTiled encode = nullptr;
    if (n_sm == 0) {
        int dev = 0;
        cudaGetDevice(&dev);
        cudaDeviceGetAttribute(&n_sm, cudaDevAttrMultiProcessorCount, dev);
        if (n_sm > MAX_CTAS) n_sm = MAX_CTAS;
        cudaFuncSetAttribute(k_stats, cudaFuncAttributeMaxDynamicSharedMemorySize, SMEM1);
        cudaFuncSetAttribute(k_main, cudaFuncAttributeMaxDynamicSharedMemorySize, SMEM2);
        cudaDriverEntryPointQueryResult qres;
        void* fn = nullptr;
        cudaGetDriverEntryPoint("cuTensorMapEncodeTiled", &fn, cudaEnableDefault, &qres);
        encode = (PFN_encodeTiled)fn;
    }
    if (last_x != x || last_w1 != w1 || last_out != d_out) {
        cuuint64_t dims[2] = {96, (cuuint64_t)NROWS};
        cuuint64_t strides[1] = {192};
        cuuint32_t box[2] = {32, 64};
        cuuint32_t es[2] = {1, 1};
        encode(&tm_x, CU_TENSOR_MAP_DATA_TYPE_BFLOAT16, 2, (void*)x, dims, strides, box, es, CU_TENSOR_MAP_INTERLEAVE_NONE,
               CU_TENSOR_MAP_SWIZZLE_64B, CU_TENSOR_MAP_L2_PROMOTION_L2_128B, CU_TENSOR_MAP_FLOAT_OOB_FILL_NONE);
        encode(&tm_out, CU_TENSOR_MAP_DATA_TYPE_BFLOAT16, 2, d_out, dims, strides, box, es, CU_TENSOR_MAP_INTERLEAVE_NONE,
               CU_TENSOR_MAP_SWIZZLE_64B, CU_TENSOR_MAP_L2_PROMOTION_L2_128B, CU_TENSOR_MAP_FLOAT_OOB_FILL_NONE);
        cuuint64_t dimsw[2] = {384, 96};
        cuuint64_t stridesw[1] = {768};
        cuuint32_t boxw[2] = {64, 96};
        encode(&tm_w1, CU_TENSOR_MAP_DATA_TYPE_BFLOAT16, 2, (void*)w1, dimsw, stridesw, boxw, es, CU_TENSOR_MAP_INTERLEAVE_NONE,
               CU_TENSOR_MAP_SWIZZLE_128B, CU_TENSOR_MAP_L2_PROMOTION_L2_128B, CU_TENSOR_MAP_FLOAT_OOB_FILL_NONE);
        last_x = x;
        last_w1 = w1;
        last_out = d_out;
    }
    k_stats<<<n_sm, NTHR, SMEM1>>>(tm_x, tm_w1, dw, w2, grn_g, grn_b);
    k_main<<<n_sm, NTHR2, SMEM2>>>(tm_x, tm_w1, tm_out, dw);
}
```

```cpp
#include <cuda_runtime.h>
#include <cuda_bf16.h>
#include <stdint.h>
#include <cuda.h>

#define C_IN 96
#define C_H 384
#define NROWS (512 * 512)
#define TILE_M 64
#define NTILES (NROWS / TILE_M)
#define MAX_CTAS 256
#define NWG 4
#define NTHR (NWG * 128)

__device__ float g_sum[C_H];
__device__ unsigned int g_done;
__device__ __align__(1024) unsigned char g_w2img[73728];
__device__ float g_c[C_IN];
#define TSTAMP(i)

#define GELU_KAPPA 0.3292034911525734f
#define GELU_C0K 2.423681954311584f

__device__ __forceinline__ uint32_t smem_u32(const void* p) { return (uint32_t)__cvta_generic_to_shared(p); }
__device__ __forceinline__ uint64_t make_desc(uint32_t addr, uint32_t lbo, uint32_t sbo, uint32_t swz = 0) {
    uint64_t d = 0;
    d |= (uint64_t)((addr & 0x3FFFF) >> 4);
    d |= (uint64_t)((lbo >> 4) & 0x3FFF) << 16;
    d |= (uint64_t)((sbo >> 4) & 0x3FFF) << 32;
    d |= (uint64_t)swz << 62;
    return d;
}
__device__ __forceinline__ void mbar_init(uint32_t bar, uint32_t count) {
    asm volatile("mbarrier.init.shared::cta.b64 [%0], %1;\n" ::"r"(bar), "r"(count) : "memory");
}
__device__ __forceinline__ void mbar_expect_tx(uint32_t bar, uint32_t bytes) {
    asm volatile("mbarrier.arrive.expect_tx.shared::cta.b64 _, [%0], %1;\n" ::"r"(bar), "r"(bytes) : "memory");
}
__device__ __forceinline__ void mbar_wait(uint32_t bar, uint32_t parity) {
    asm volatile(
        "{\n.reg .pred p;\n"
        "WAIT_LOOP:\n"
        "mbarrier.try_wait.parity.shared::cta.b64 p, [%0], %1;\n"
        "@p bra WAIT_DONE;\n"
        "bra WAIT_LOOP;\n"
        "WAIT_DONE:\n}\n" ::"r"(bar), "r"(parity) : "memory");
}
__device__ __forceinline__ void tma_load_2d(uint32_t dst, const CUtensorMap* tm, uint32_t bar, int c0, int c1) {
    asm volatile(
        "cp.async.bulk.tensor.2d.shared::cluster.global.mbarrier::complete_tx::bytes [%0], [%1, {%3, %4}], [%2];\n" ::"r"(dst),
        "l"(reinterpret_cast<uint64_t>(tm)), "r"(bar), "r"(c0), "r"(c1)
        : "memory");
}
__device__ __forceinline__ void wg_fence() { asm volatile("wgmma.fence.sync.aligned;\n" ::: "memory"); }
__device__ __forceinline__ void wg_commit() { asm volatile("wgmma.commit_group.sync.aligned;\n" ::: "memory"); }
template <int N>
__device__ __forceinline__ void wg_wait() { asm volatile("wgmma.wait_group.sync.aligned %0;\n" ::"n"(N) : "memory"); }
__device__ __forceinline__ void wg_bar(int id) { asm volatile("bar.sync %0, 128;" ::"r"(id) : "memory"); }
__device__ __forceinline__ void proxy_fence() {
 asm volatile("fence.proxy.async.shared::cta;\n" ::: "memory"); }
__device__ __forceinline__ void cp_async16(uint32_t dst, const void* src) {
    asm volatile("cp.async.cg.shared.global [%0], [%1], 16;\n" ::"r"(dst), "l"(src) : "memory");
}
__device__ __forceinline__ void cp_async_commit() { asm volatile("cp.async.commit_group;\n" ::: "memory"); }
__device__ __forceinline__ void cp_async_wait_all() { asm volatile("cp.async.wait_group 0;\n" ::: "memory"); }
__device__ __forceinline__ void prefetch_l2(const void* p) { asm volatile("prefetch.global.L2 [%0];\n" ::"l"(p)); }

__device__ __forceinline__ float tanh_approx(float x) {
    float y;
    asm("tanh.approx.f32 %0, %1;" : "=f"(y) : "f"(x));
    return y;
}
__device__ __forceinline__ uint32_t pack_bf16(float lo, float hi) {
    uint32_t r;
    asm("cvt.rn.bf16x2.f32 %0, %1, %2;" : "=r"(r) : "f"(hi), "f"(lo));
    return r;
}
__device__ __forceinline__ float bf_lo(uint32_t v) { return __uint_as_float(v << 16); }
__device__ __forceinline__ float bf_hi(uint32_t v) { return __uint_as_float(v & 0xffff0000u); }

#define ACC32(d)                                                                                             \
    "+f"(d[0]), "+f"(d[1]), "+f"(d[2]), "+f"(d[3]), "+f"(d[4]), "+f"(d[5]), "+f"(d[6]), "+f"(d[7]),          \
        "+f"(d[8]), "+f"(d[9]), "+f"(d[10]), "+f"(d[11]), "+f"(d[12]), "+f"(d[13]), "+f"(d[14]), "+f"(d[15]), \
        "+f"(d[16]), "+f"(d[17]), "+f"(d[18]), "+f"(d[19]), "+f"(d[20]), "+f"(d[21]), "+f"(d[22]),           \
        "+f"(d[23]), "+f"(d[24]), "+f"(d[25]), "+f"(d[26]), "+f"(d[27]), "+f"(d[28]), "+f"(d[29]),           \
        "+f"(d[30]), "+f"(d[31])
#define ACC32_STR                                                                \
    "{%0, %1, %2, %3, %4, %5, %6, %7, %8, %9, %10, %11, %12, %13, %14, %15, "    \
    " %16, %17, %18, %19, %20, %21, %22, %23, %24, %25, %26, %27, %28, %29, %30, %31}"

__device__ __forceinline__ void wgmma_ss_n64_tA(float (&d)[32], uint64_t adesc, uint64_t bdesc, int scale_d) {
    asm volatile(
        "{\n.reg .pred p;\nsetp.ne.b32 p, %34, 0;\n"
        "wgmma.mma_async.sync.aligned.m64n64k16.f32.bf16.bf16 " ACC32_STR ", %32, %33, p, 1, 1, 1, 0;\n}\n"
        : ACC32(d)
        : "l"(adesc), "l"(bdesc), "r"(scale_d));
}
__device__ __forceinline__ void wgmma_ss_n64(float (&d)[32], uint64_t adesc, uint64_t bdesc, int scale_d) {
    asm volatile(
        "{\n.reg .pred p;\nsetp.ne.b32 p, %34, 0;\n"
        "wgmma.mma_async.sync.aligned.m64n64k16.f32.bf16.bf16 " ACC32_STR ", %32, %33, p, 1, 1, 0, 1;\n}\n"
        : ACC32(d)
        : "l"(adesc), "l"(bdesc), "r"(scale_d));
}
__device__ __forceinline__ void wgmma_n96(float (&d)[48], uint32_t a0, uint32_t a1, uint32_t a2, uint32_t a3,
                                          uint64_t bdesc) {
    asm volatile(
        "{\n"
        "wgmma.mma_async.sync.aligned.m64n96k16.f32.bf16.bf16 "
        "{%0, %1, %2, %3, %4, %5, %6, %7, %8, %9, %10, %11, %12, %13, %14, %15, "
        " %16, %17, %18, %19, %20, %21, %22, %23, %24, %25, %26, %27, %28, %29, %30, %31, "
        " %32, %33, %34, %35, %36, %37, %38, %39, %40, %41, %42, %43, %44, %45, %46, %47}, "
        "{%48, %49, %50, %51}, %52, 1, 1, 1, 1;\n"
        "}\n"
        : ACC32(d), "+f"(d[32]), "+f"(d[33]), "+f"(d[34]), "+f"(d[35]), "+f"(d[36]), "+f"(d[37]), "+f"(d[38]),
          "+f"(d[39]), "+f"(d[40]), "+f"(d[41]), "+f"(d[42]), "+f"(d[43]), "+f"(d[44]), "+f"(d[45]), "+f"(d[46]),
          "+f"(d[47])
        : "r"(a0), "r"(a1), "r"(a2), "r"(a3), "l"(bdesc));
}

#define W2_LBO 128
#define W2_SBO (48 * 128)
#define W1_BOX_BYTES (96 * 128)
#define Y_BOX_BYTES (64 * 64)
#define Y_TILE_BYTES (3 * Y_BOX_BYTES)

__device__ __forceinline__ void ln_row4(const uint4 (&xv)[3], const float* __restrict__ s_dwq, uint4 (&y)[3]) {
    float xf[24], dwf[24];
    float s = 0.f;
#pragma unroll
    for (int i = 0; i < 3; i++) {
        uint32_t w[4] = {xv[i].x, xv[i].y, xv[i].z, xv[i].w};
        float4 da = *reinterpret_cast<const float4*>(s_dwq + 32 * i);
        float4 db = *reinterpret_cast<const float4*>(s_dwq + 32 * i + 4);
        dwf[i * 8 + 0] = da.x; dwf[i * 8 + 1] = da.y; dwf[i * 8 + 2] = da.z; dwf[i * 8 + 3] = da.w;
        dwf[i * 8 + 4] = db.x; dwf[i * 8 + 5] = db.y; dwf[i * 8 + 6] = db.z; dwf[i * 8 + 7] = db.w;
#pragma unroll
        for (int p = 0; p < 4; p++) {
            xf[i * 8 + 2 * p] = bf_lo(w[p]);
            xf[i * 8 + 2 * p + 1] = bf_hi(w[p]);
        }
#pragma unroll
        for (int p = 0; p < 8; p++) s = fmaf(xf[i * 8 + p], dwf[i * 8 + p], s);
    }
    s += __shfl_xor_sync(0xffffffffu, s, 1);
    s += __shfl_xor_sync(0xffffffffu, s, 2);
    float nmean = s * (-1.0f / C_IN);
    float v = 0.f;
#pragma unroll
    for (int i = 0; i < 24; i++) {
        xf[i] = fmaf(xf[i], dwf[i], nmean);
        v = fmaf(xf[i], xf[i], v);
    }
    v += __shfl_xor_sync(0xffffffffu, v, 1);
    v += __shfl_xor_sync(0xffffffffu, v, 2);
    float rstd = rsqrtf(v * (1.0f / C_IN) + 1e-5f) * GELU_KAPPA;
#pragma unroll
    for (int i = 0; i < 3; i++) {
        y[i].x = pack_bf16(xf[i * 8 + 0] * rstd, xf[i * 8 + 1] * rstd);
        y[i].y = pack_bf16(xf[i * 8 + 2] * rstd, xf[i * 8 + 3] * rstd);
        y[i].z = pack_bf16(xf[i * 8 + 4] * rstd, xf[i * 8 + 5] * rstd);
        y[i].w = pack_bf16(xf[i * 8 + 6] * rstd, xf[i * 8 + 7] * rstd);
    }
}

__device__ __forceinline__ void ln_tile_inplace(unsigned char* yp, const float* __restrict__ s_dwq) {
    uint4 xv[3], y[3];
#pragma unroll
    for (int i = 0; i < 3; i++) xv[i] = *reinterpret_cast<const uint4*>(yp + i * Y_BOX_BYTES);
    ln_row4(xv, s_dwq, y);
#pragma unroll
    for (int i = 0; i < 3; i++) *reinterpret_cast<uint4*>(yp + i * Y_BOX_BYTES) = y[i];
#pragma unroll
    for (int i = 0; i < 3; i++) xv[i] = *reinterpret_cast<const uint4*>(yp + 512 + i * Y_BOX_BYTES);
    ln_row4(xv, s_dwq, y);
#pragma unroll
    for (int i = 0; i < 3; i++) *reinterpret_cast<uint4*>(yp + 512 + i * Y_BOX_BYTES) = y[i];
}

__device__ __forceinline__ float gelu2(float u) {
    float t = fmaf(u, u, GELU_C0K);
    float a = t * u;
    float th = tanh_approx(a);
    return fmaf(u, th, u);
}

__device__ __forceinline__ void tma_x_tile(uint32_t dst, const CUtensorMap* tmx, uint32_t bar, int tile) {
    mbar_expect_tx(bar, Y_TILE_BYTES);
#pragma unroll
    for (int i = 0; i < 3; i++) tma_load_2d(dst + i * Y_BOX_BYTES, tmx, bar, i * 32, tile * TILE_M);
}

__global__ void __launch_bounds__(NTHR, 1)
k_stats(const __grid_constant__ CUtensorMap tm_x, const __grid_constant__ CUtensorMap tm_w1,
        const __nv_bfloat16* __restrict__ dw, const __nv_bfloat16* __restrict__ w2,
        const __nv_bfloat16* __restrict__ grn_g, const __nv_bfloat16* __restrict__ grn_b) {
    extern __shared__ __align__(1024) unsigned char smem[];
    unsigned char* s_w1 = smem;
    unsigned char* s_y = smem + 73728;
    float* s_dw = reinterpret_cast<float*>(smem + 73728 + NWG * 2 * Y_TILE_BYTES);
    float* s_red = s_dw + 128;
    uint64_t* s_bar = reinterpret_cast<uint64_t*>(s_red + C_H);

    const int tid = threadIdx.x;
    const int wg = tid >> 7;
    const int warp = (tid >> 5) & 3;
    const int lane = tid & 31;
    const int q = lane & 3;
    const int nwg = gridDim.x * NWG;
    int tile = blockIdx.x * NWG + wg;

    if (tid == 0) {
        for (int i = 0; i < 1 + 2 * NWG; i++) mbar_init(smem_u32(s_bar + i), 1);
        asm volatile("fence.mbarrier_init.release.cluster;\n" ::: "memory");
    }
    if (tid < C_IN) s_dw[tid] = __bfloat162float(dw[tid]);
    for (int i = tid; i < C_H; i += NTHR) s_red[i] = 0.f;
    __syncthreads();
    const uint32_t ybuf0 = smem_u32(s_y + wg * 2 * Y_TILE_BYTES);
    const uint32_t bar_y = smem_u32(s_bar + 1 + 2 * wg);
    if (tid == 0) {
        mbar_expect_tx(smem_u32(s_bar), 6 * W1_BOX_BYTES);
        for (int i = 0; i < 6; i++) tma_load_2d(smem_u32(s_w1) + i * W1_BOX_BYTES, &tm_w1, smem_u32(s_bar), i * 64, 0);
    }
    if ((tid & 127) == 0 && tile < NTILES) tma_x_tile(ybuf0, &tm_x, bar_y, tile);

    if (blockIdx.x == 0) {
        prefetch_l2(reinterpret_cast<const unsigned char*>(w2) + tid * 128);
        if (tid < 64) prefetch_l2(reinterpret_cast<const unsigned char*>(w2) + (512 + tid) * 128);
    }
    float ss[12];
#pragma unroll
    for (int i = 0; i < 12; i++) ss[i] = 0.f;

    const uint64_t w1_desc = make_desc(smem_u32(s_w1), W1_BOX_BYTES, 1024, 1);
    const int rl = warp * 16 + (lane >> 2);
    const int yoff = rl * 64 + ((q ^ ((rl >> 1) & 3)) * 16);
    mbar_wait(smem_u32(s_bar), 0);

    int it = 0;
    for (; tile < NTILES; tile += nwg, it++) {
        const int buf = it & 1;
        if ((tid & 127) == 0 && tile + nwg < NTILES) tma_x_tile(ybuf0 + (buf ^ 1) * Y_TILE_BYTES, &tm_x, bar_y + (buf ^ 1) * 8, tile + nwg);
        mbar_wait(bar_y + buf * 8, (it >> 1) & 1);
        unsigned char* ytile = s_y + (wg * 2 + buf) * Y_TILE_BYTES;
        ln_tile_inplace(ytile + yoff, s_dw + 8 * q);
        proxy_fence();
        wg_bar(1 + wg);
        const uint64_t y_desc = make_desc(smem_u32(ytile), 16, 512, 2);
        float S[2][32];
        wg_fence();
#pragma unroll
        for (int t = 0; t < 6; t++)
            wgmma_ss_n64_tA(S[0], w1_desc + ((t * 2048) >> 4), y_desc + (((t >> 1) * Y_BOX_BYTES + (t & 1) * 32) >> 4), t != 0);
        wg_commit();
#pragma unroll
        for (int m = 0; m < 6; m++) {
            if (m + 1 < 6) {
                wg_fence();
#pragma unroll
                for (int t = 0; t < 6; t++)
                    wgmma_ss_n64_tA(S[(m + 1) & 1], w1_desc + (((m + 1) * W1_BOX_BYTES + t * 2048) >> 4),
                                    y_desc + (((t >> 1) * Y_BOX_BYTES + (t & 1) * 32) >> 4), t != 0);
                wg_commit();
                wg_wait<1>();
            } else {
                wg_wait<0>();
            }
            float(&Sc)[32] = S[m & 1];
            float a0 = ss[2 * m], a1 = ss[2 * m + 1];
#pragma unroll
            for (int j = 0; j < 8; j++) {
                float g0 = gelu2(Sc[4 * j]);
                float g1 = gelu2(Sc[4 * j + 1]);
                float g2 = gelu2(Sc[4 * j + 2]);
                float g3 = gelu2(Sc[4 * j + 3]);
                a0 = fmaf(g0, g0, a0);
                a1 = fmaf(g2, g2, a1);
                a0 = fmaf(g1, g1, a0);
                a1 = fmaf(g3, g3, a1);
            }
            ss[2 * m] = a0;
            ss[2 * m + 1] = a1;
        }
        wg_bar(1 + wg);
    }
#pragma unroll
    for (int i = 0; i < 12; i++) {
        float v = ss[i];
        v += __shfl_xor_sync(0xffffffffu, v, 1);
        v += __shfl_xor_sync(0xffffffffu, v, 2);
        if (q == 0) {
            int m = i >> 1, hh = i & 1;
            atomicAdd(&s_red[m * 64 + warp * 16 + hh * 8 + (lane >> 2)], v);
        }
    }
    __syncthreads();
    const float sc = 0.25f / (GELU_KAPPA * GELU_KAPPA);
    for (int i = tid; i < C_H; i += NTHR) atomicAdd(&g_sum[i], s_red[i] * sc);
    __threadfence();
    __syncthreads();
    __shared__ unsigned int s_last;
    if (tid == 0) s_last = (atomicAdd(&g_done, 1u) == gridDim.x - 1);
    __syncthreads();
    if (!s_last) return;
    __threadfence();
    uint4 w2v[384 * 12 / NTHR];
#pragma unroll
    for (int i = 0; i < 384 * 12 / NTHR; i++) {
        int it2 = tid + i * NTHR;
        int kr = it2 & 7;
        int nb = (it2 >> 3) % 12;
        int kb = (it2 >> 3) / 12;
        w2v[i] = __ldg(reinterpret_cast<const uint4*>(w2 + (kb * 8 + kr) * C_IN + nb * 8));
    }
    float* s_s = s_red;
    float* s_tmp = s_dw;
    float lsum = 0.f;
    if (tid < C_H) {
        float gx = sqrtf(__ldcg(&g_sum[tid]) + 1e-6f);
        g_sum[tid] = 0.f;
        s_s[tid] = gx;
        lsum = gx;
    }
#pragma unroll
    for (int o = 16; o > 0; o >>= 1) lsum += __shfl_xor_sync(0xffffffffu, lsum, o);
    if (lane == 0) s_tmp[tid >> 5] = lsum;
    if (tid == 0) g_done = 0;
    __syncthreads();
    float tot = 0.f;
#pragma unroll
    for (int i = 0; i < NTHR / 32; i++) tot += s_tmp[i];
    float inv = 1.0f / (tot * (1.0f / C_H) + 1e-6f);
    __syncthreads();
    if (tid < C_H) s_s[tid] = (0.5f / GELU_KAPPA) * (1.0f + __bfloat162float(grn_g[tid]) * (s_s[tid] * inv));
    if (tid < C_IN) s_tmp[tid] = 0.f;
    __syncthreads();
    {
        float a0 = 0.f, a1 = 0.f, a2 = 0.f;
        int kbase = (tid >> 5) * (C_H / (NTHR / 32));
#pragma unroll
        for (int k = kbase; k < kbase + C_H / (NTHR / 32); k++) {
            float b = __bfloat162float(grn_b[k]);
            a0 = fmaf(b, __bfloat162float(w2[k * C_IN + lane]), a0);
            a1 = fmaf(b, __bfloat162float(w2[k * C_IN + lane + 32]), a1);
            a2 = fmaf(b, __bfloat162float(w2[k * C_IN + lane + 64]), a2);
        }
        atomicAdd(&s_tmp[lane], a0);
        atomicAdd(&s_tmp[lane + 32], a1);
        atomicAdd(&s_tmp[lane + 64], a2);
    }
#pragma unroll
    for (int i = 0; i < 384 * 12 / NTHR; i++) {
        int it2 = tid + i * NTHR;
        int kr = it2 & 7;
        int nb = (it2 >> 3) % 12;
        int kb = (it2 >> 3) / 12;
        float sk = s_s[kb * 8 + kr];
        uint4 v = w2v[i];
        uint4 o;
        o.x = pack_bf16(sk * bf_lo(v.x), sk * bf_hi(v.x));
        o.y = pack_bf16(sk * bf_lo(v.y), sk * bf_hi(v.y));
        o.z = pack_bf16(sk * bf_lo(v.z), sk * bf_hi(v.z));
        o.w = pack_bf16(sk * bf_lo(v.w), sk * bf_hi(v.w));
        *reinterpret_cast<uint4*>(g_w2img + nb * W2_SBO + kb * W2_LBO + kr * 16) = o;
    }
    __syncthreads();
    if (tid < C_IN) g_c[tid] = s_tmp[tid];
}

#define NWG2 2
#define NTHR2 (NWG2 * 128)

__device__ __forceinline__ void wgmma_rs_n64(float (&d)[32], uint32_t a0, uint32_t a1, uint32_t a2, uint32_t a3,
                                             uint64_t bdesc, int scale_d) {
    asm volatile(
        "{\n.reg .pred p;\nsetp.ne.b32 p, %37, 0;\n"
        "wgmma.mma_async.sync.aligned.m64n64k16.f32.bf16.bf16 " ACC32_STR ", {%32, %33, %34, %35}, %36, p, 1, 1, 1;\n}\n"
        : ACC32(d)
        : "r"(a0), "r"(a1), "r"(a2), "r"(a3), "l"(bdesc), "r"(scale_d));
}
__device__ __forceinline__ void ldsm_x4(uint32_t addr, uint32_t& r0, uint32_t& r1, uint32_t& r2, uint32_t& r3) {
    asm volatile("ldmatrix.sync.aligned.m8n8.x4.shared.b16 {%0, %1, %2, %3}, [%4];\n"
                 : "=r"(r0), "=r"(r1), "=r"(r2), "=r"(r3) : "r"(addr) : "memory");
}
__device__ __forceinline__ void stsm_x4(uint32_t addr, uint32_t r0, uint32_t r1, uint32_t r2, uint32_t r3) {
    asm volatile("stmatrix.sync.aligned.m8n8.x4.shared.b16 [%0], {%1, %2, %3, %4};\n" ::"r"(addr), "r"(r0), "r"(r1), "r"(r2),
                 "r"(r3) : "memory");
}
__device__ __forceinline__ void tma_store_2d(const CUtensorMap* tm, uint32_t src, int c0, int c1) {
    asm volatile("cp.async.bulk.tensor.2d.global.shared::cta.bulk_group [%0, {%2, %3}], [%1];\n" ::"l"(
                     reinterpret_cast<uint64_t>(tm)), "r"(src), "r"(c0), "r"(c1) : "memory");
}

__device__ __forceinline__ void ln_frag(uint32_t (&f)[6][4], const float* __restrict__ s_dwq) {
    float xa[24], xb[24], dwf[24];
    float sa = 0.f, sb = 0.f;
#pragma unroll
    for (int t = 0; t < 6; t++) {
#pragma unroll
        for (int h = 0; h < 2; h++) {
            float2 d = *reinterpret_cast<const float2*>(s_dwq + 16 * t + 8 * h);
            int i = t * 4 + h * 2;
            dwf[i] = d.x; dwf[i + 1] = d.y;
            xa[i] = bf_lo(f[t][2 * h]); xa[i + 1] = bf_hi(f[t][2 * h]);
            xb[i] = bf_lo(f[t][2 * h + 1]); xb[i + 1] = bf_hi(f[t][2 * h + 1]);
            sa = fmaf(xa[i], d.x, sa); sa = fmaf(xa[i + 1], d.y, sa);
            sb = fmaf(xb[i], d.x, sb); sb = fmaf(xb[i + 1], d.y, sb);
        }
    }
    sa += __shfl_xor_sync(0xffffffffu, sa, 1);
    sb += __shfl_xor_sync(0xffffffffu, sb, 1);
    sa += __shfl_xor_sync(0xffffffffu, sa, 2);
    sb += __shfl_xor_sync(0xffffffffu, sb, 2);
    float ma = sa * (-1.0f / C_IN), mb = sb * (-1.0f / C_IN);
    float va = 0.f, vb = 0.f;
#pragma unroll
    for (int i = 0; i < 24; i++) {
        xa[i] = fmaf(xa[i], dwf[i], ma);
        xb[i] = fmaf(xb[i], dwf[i], mb);
        va = fmaf(xa[i], xa[i], va);
        vb = fmaf(xb[i], xb[i], vb);
    }
    va += __shfl_xor_sync(0xffffffffu, va, 1);
    vb += __shfl_xor_sync(0xffffffffu, vb, 1);
    va += __shfl_xor_sync(0xffffffffu, va, 2);
    vb += __shfl_xor_sync(0xffffffffu, vb, 2);
    float ra = rsqrtf(va * (1.0f / C_IN) + 1e-5f) * GELU_KAPPA;
    float rb = rsqrtf(vb * (1.0f / C_IN) + 1e-5f) * GELU_KAPPA;
#pragma unroll
    for (int t = 0; t < 6; t++) {
#pragma unroll
        for (int h = 0; h < 2; h++) {
            int i = t * 4 + h * 2;
            f[t][2 * h] = pack_bf16(xa[i] * ra, xa[i + 1] * ra);
            f[t][2 * h + 1] = pack_bf16(xb[i] * rb, xb[i + 1] * rb);
        }
    }
}

__global__ void __launch_bounds__(NTHR2, 1)
k_main(const __grid_constant__ CUtensorMap tm_x, const __grid_constant__ CUtensorMap tm_w1,
       const __grid_constant__ CUtensorMap tm_out, const __nv_bfloat16* __restrict__ dw) {
    extern __shared__ __align__(1024) unsigned char smem[];
    unsigned char* s_w1 = smem;
    unsigned char* s_w2 = smem + 73728;
    unsigned char* s_x = smem + 2 * 73728;
    float* s_dw = reinterpret_cast<float*>(smem + 2 * 73728 + NWG2 * 2 * Y_TILE_BYTES);
    float* s_c = s_dw + 128;
    uint64_t* s_bar = reinterpret_cast<uint64_t*>(s_c + 128);

    const int tid = threadIdx.x;
    const int wg = tid >> 7;
    const int warp = (tid >> 5) & 3;
    const int lane = tid & 31;
    const int q = lane & 3;
    const int nwg = gridDim.x * NWG2;
    int tile = blockIdx.x * NWG2 + wg;

    const uint32_t xbuf0 = smem_u32(s_x + wg * 2 * Y_TILE_BYTES);
    const uint32_t bar_x = smem_u32(s_bar + 1 + 2 * wg);
    if (tid == 0) {
        for (int i = 0; i < 1 + 2 * NWG2; i++) mbar_init(smem_u32(s_bar + i), 1);
        asm volatile("fence.mbarrier_init.release.cluster;\n" ::: "memory");
    }
    if (tid < C_IN) { s_dw[tid] = __bfloat162float(dw[tid]); s_c[tid] = g_c[tid]; }
    __syncthreads();
    if (tid == 0) {
        mbar_expect_tx(smem_u32(s_bar), 6 * W1_BOX_BYTES + 73728);
        for (int i = 0; i < 6; i++) tma_load_2d(smem_u32(s_w1) + i * W1_BOX_BYTES, &tm_w1, smem_u32(s_bar), i * 64, 0);
        for (int i = 0; i < 6; i++)
            asm volatile("cp.async.bulk.shared::cluster.global.mbarrier::complete_tx::bytes [%0], [%1], %2, [%3];\n" ::"r"(
                             smem_u32(s_w2) + i * 12288),
                         "l"(g_w2img + i * 12288), "r"(12288), "r"(smem_u32(s_bar))
                         : "memory");
    }
    if ((tid & 127) == 0 && tile < NTILES) tma_x_tile(xbuf0, &tm_x, bar_x, tile);
    mbar_wait(smem_u32(s_bar), 0);

    const uint64_t w1_desc = make_desc(smem_u32(s_w1), W1_BOX_BYTES, 1024, 1);
    const uint64_t w2_desc = make_desc(smem_u32(s_w2), W2_LBO, W2_SBO, 0);
    const int lrow = warp * 16 + ((lane >> 3) & 1) * 8 + (lane & 7);
    const int lhalf = lane >> 4;
    const int lsw = (lrow >> 1) & 3;
    const uint32_t loff0 = lrow * 64 + (((0 + lhalf) ^ lsw) << 4);
    const uint32_t loff1 = lrow * 64 + (((2 + lhalf) ^ lsw) << 4);

    int it = 0;
    for (; tile < NTILES; tile += nwg, it++) {
        const int buf = it & 1;
        const uint32_t xb = xbuf0 + buf * Y_TILE_BYTES;
        if ((tid & 127) == 0 && tile + nwg < NTILES) {
            asm volatile("cp.async.bulk.wait_group.read 0;\n" ::: "memory");
            tma_x_tile(xbuf0 + (buf ^ 1) * Y_TILE_BYTES, &tm_x, bar_x + (buf ^ 1) * 8, tile + nwg);
        }
        mbar_wait(bar_x + buf * 8, (it >> 1) & 1);
        uint32_t f[6][4];
#pragma unroll
        for (int t = 0; t < 6; t++)
            ldsm_x4(xb + (t >> 1) * Y_BOX_BYTES + ((t & 1) ? loff1 : loff0), f[t][0], f[t][1], f[t][2], f[t][3]);
        ln_frag(f, s_dw + 2 * q);

        float O[48];
#pragma unroll
        for (int j = 0; j < 12; j++) {
            float2 cc = *reinterpret_cast<const float2*>(&s_c[8 * j + 2 * q]);
            O[4 * j] = cc.x; O[4 * j + 1] = cc.y; O[4 * j + 2] = cc.x; O[4 * j + 3] = cc.y;
        }
        float S[2][32];
        uint32_t hf[2][16];
        wg_fence();
#pragma unroll
        for (int t = 0; t < 6; t++) wgmma_rs_n64(S[0], f[t][0], f[t][1], f[t][2], f[t][3], w1_desc + ((t * 2048) >> 4), t != 0);
        wg_commit();
#pragma unroll
        for (int c = 0; c < 6; c++) {
            if (c + 1 < 6) {
                wg_fence();
#pragma unroll
                for (int t = 0; t < 6; t++)
                    wgmma_rs_n64(S[(c + 1) & 1], f[t][0], f[t][1], f[t][2], f[t][3],
                                 w1_desc + (((c + 1) * W1_BOX_BYTES + t * 2048) >> 4), t != 0);
                wg_commit();
                if (c == 0) wg_wait<1>(); else wg_wait<2>();
            } else {
                wg_wait<1>();
            }
            float(&Sc)[32] = S[c & 1];
            uint32_t(&h)[16] = hf[c & 1];
#pragma unroll
            for (int j = 0; j < 8; j++) {
                float g0 = gelu2(Sc[4 * j]);
                float g1 = gelu2(Sc[4 * j + 1]);
                float g2 = gelu2(Sc[4 * j + 2]);
                float g3 = gelu2(Sc[4 * j + 3]);
                h[2 * j] = pack_bf16(g0, g1);
                h[2 * j + 1] = pack_bf16(g2, g3);
            }
            wg_fence();
#pragma unroll
            for (int t = 0; t < 4; t++)
                wgmma_n96(O, h[4 * t], h[4 * t + 1], h[4 * t + 2], h[4 * t + 3],
                          w2_desc + (((c * 8 + 2 * t) * W2_LBO) >> 4));
            wg_commit();
        }
        uint32_t xr[6][4];
#pragma unroll
        for (int t = 0; t < 6; t++)
            ldsm_x4(xb + (t >> 1) * Y_BOX_BYTES + ((t & 1) ? loff1 : loff0), xr[t][0], xr[t][1], xr[t][2], xr[t][3]);
        wg_wait<0>();
#pragma unroll
        for (int t = 0; t < 6; t++) {
            uint32_t o0 = pack_bf16(bf_lo(xr[t][0]) + O[8 * t + 0], bf_hi(xr[t][0]) + O[8 * t + 1]);
            uint32_t o1 = pack_bf16(bf_lo(xr[t][1]) + O[8 * t + 2], bf_hi(xr[t][1]) + O[8 * t + 3]);
            uint32_t o2 = pack_bf16(bf_lo(xr[t][2]) + O[8 * t + 4], bf_hi(xr[t][2]) + O[8 * t + 5]);
            uint32_t o3 = pack_bf16(bf_lo(xr[t][3]) + O[8 * t + 6], bf_hi(xr[t][3]) + O[8 * t + 7]);
            stsm_x4(xb + (t >> 1) * Y_BOX_BYTES + ((t & 1) ? loff1 : loff0), o0, o1, o2, o3);
        }
        proxy_fence();
        wg_bar(1 + wg);
        if ((tid & 127) == 0) {
#pragma unroll
            for (int i = 0; i < 3; i++) tma_store_2d(&tm_out, xb + i * Y_BOX_BYTES, i * 32, tile * TILE_M);
            asm volatile("cp.async.bulk.commit_group;\n" ::: "memory");
        }
    }
    if ((tid & 127) == 0) asm volatile("cp.async.bulk.wait_group 0;\n" ::: "memory");
}

#define SMEM1 (73728 + NWG * 2 * Y_TILE_BYTES + 512 + 1536 + 128)
#define SMEM2 (2 * 73728 + NWG2 * 2 * Y_TILE_BYTES + 512 + 512 + 64)

typedef CUresult (*PFN_encodeTiled)(CUtensorMap*, CUtensorMapDataType, cuuint32_t, void*, const cuuint64_t*, const cuuint64_t*,
                                    const cuuint32_t*, const cuuint32_t*, CUtensorMapInterleave, CUtensorMapSwizzle,
                                    CUtensorMapL2promotion, CUtensorMapFloatOOBfill);

extern "C" void kernel_launch(void* const* d_in, const int* in_sizes, int n_in, void* d_out, int out_size) {
    const __nv_bfloat16* x = (const __nv_bfloat16*)d_in[0];
    const __nv_bfloat16* dw = (const __nv_bfloat16*)d_in[1];
    const __nv_bfloat16* w1 = (const __nv_bfloat16*)d_in[2];
    const __nv_bfloat16* w2 = (const __nv_bfloat16*)d_in[3];
    const __nv_bfloat16* grn_g = (const __nv_bfloat16*)d_in[4];
    const __nv_bfloat16* grn_b = (const __nv_bfloat16*)d_in[5];

    static int n_sm = 0;
    static CUtensorMap tm_x, tm_w1, tm_out;
    static const void* last_x = nullptr;
    static const void* last_w1 = nullptr;
    static const void* last_out = nullptr;
    static PFN_encodeTiled encode = nullptr;
    if (n_sm == 0) {
        int dev = 0;
        cudaGetDevice(&dev);
        cudaDeviceGetAttribute(&n_sm, cudaDevAttrMultiProcessorCount, dev);
        if (n_sm > MAX_CTAS) n_sm = MAX_CTAS;
        cudaFuncSetAttribute(k_stats, cudaFuncAttributeMaxDynamicSharedMemorySize, SMEM1);
        cudaFuncSetAttribute(k_main, cudaFuncAttributeMaxDynamicSharedMemorySize, SMEM2);
        cudaDriverEntryPointQueryResult qres;
        void* fn = nullptr;
        cudaGetDriverEntryPoint("cuTensorMapEncodeTiled", &fn, cudaEnableDefault, &qres);
        encode = (PFN_encodeTiled)fn;
    }
    if (last_x != x || last_w1 != w1 || last_out != d_out) {
        cuuint64_t dims[2] = {96, (cuuint64_t)NROWS};
        cuuint64_t strides[1] = {192};
        cuuint32_t box[2] = {32, 64};
        cuuint32_t es[2] = {1, 1};
        encode(&tm_x, CU_TENSOR_MAP_DATA_TYPE_BFLOAT16, 2, (void*)x, dims, strides, box, es, CU_TENSOR_MAP_INTERLEAVE_NONE,
               CU_TENSOR_MAP_SWIZZLE_64B, CU_TENSOR_MAP_L2_PROMOTION_L2_128B, CU_TENSOR_MAP_FLOAT_OOB_FILL_NONE);
        encode(&tm_out, CU_TENSOR_MAP_DATA_TYPE_BFLOAT16, 2, d_out, dims, strides, box, es, CU_TENSOR_MAP_INTERLEAVE_NONE,
               CU_TENSOR_MAP_SWIZZLE_64B, CU_TENSOR_MAP_L2_PROMOTION_L2_128B, CU_TENSOR_MAP_FLOAT_OOB_FILL_NONE);
        cuuint64_t dimsw[2] = {384, 96};
        cuuint64_t stridesw[1] = {768};
        cuuint32_t boxw[2] = {64, 96};
        encode(&tm_w1, CU_TENSOR_MAP_DATA_TYPE_BFLOAT16, 2, (void*)w1, dimsw, stridesw, boxw, es, CU_TENSOR_MAP_INTERLEAVE_NONE,
               CU_TENSOR_MAP_SWIZZLE_128B, CU_TENSOR_MAP_L2_PROMOTION_L2_128B, CU_TENSOR_MAP_FLOAT_OOB_FILL_NONE);
        last_x = x;
        last_w1 = w1;
        last_out = d_out;
    }
    k_stats<<<n_sm, NTHR, SMEM1>>>(tm_x, tm_w1, dw, w2, grn_g, grn_b);
    k_main<<<n_sm, NTHR2, SMEM2>>>(tm_x, tm_w1, tm_out, dw);
}
```

```cpp
#include <cuda_runtime.h>
#include <cuda_bf16.h>
#include <stdint.h>
#include <cuda.h>

#define C_IN 96
#define C_H 384
#define NROWS (512 * 512)
#define TILE_M 64
#define NTILES (NROWS / TILE_M)
#define MAX_CTAS 256
#define NWG 4
#define NTHR (NWG * 128)

__device__ float g_sum[C_H];
__device__ unsigned int g_done;

#define TSTAMP(i)

#define GELU_KAPPA 0.3292034911525734f
#define GELU_C0K 2.423681954311584f

__device__ __forceinline__ uint32_t smem_u32(const void* p) { return (uint32_t)__cvta_generic_to_shared(p); }
__device__ __forceinline__ uint64_t make_desc(uint32_t addr, uint32_t lbo, uint32_t sbo, uint32_t swz = 0) {
    uint64_t d = 0;
    d |= (uint64_t)((addr & 0x3FFFF) >> 4);
    d |= (uint64_t)((lbo >> 4) & 0x3FFF) << 16;
    d |= (uint64_t)((sbo >> 4) & 0x3FFF) << 32;
    d |= (uint64_t)swz << 62;
    return d;
}
__device__ __forceinline__ void mbar_init(uint32_t bar, uint32_t count) {
    asm volatile("mbarrier.init.shared::cta.b64 [%0], %1;\n" ::"r"(bar), "r"(count) : "memory");
}
__device__ __forceinline__ void mbar_expect_tx(uint32_t bar, uint32_t bytes) {
    asm volatile("mbarrier.arrive.expect_tx.shared::cta.b64 _, [%0], %1;\n" ::"r"(bar), "r"(bytes) : "memory");
}
__device__ __forceinline__ void mbar_wait(uint32_t bar, uint32_t parity) {
    asm volatile(
        "{\n.reg .pred p;\n"
        "WAIT_LOOP:\n"
        "mbarrier.try_wait.parity.shared::cta.b64 p, [%0], %1;\n"
        "@p bra WAIT_DONE;\n"
        "bra WAIT_LOOP;\n"
        "WAIT_DONE:\n}\n" ::"r"(bar), "r"(parity) : "memory");
}
__device__ __forceinline__ void tma_load_2d(uint32_t dst, const CUtensorMap* tm, uint32_t bar, int c0, int c1) {
    asm volatile(
        "cp.async.bulk.tensor.2d.shared::cluster.global.mbarrier::complete_tx::bytes [%0], [%1, {%3, %4}], [%2];\n" ::"r"(dst),
        "l"(reinterpret_cast<uint64_t>(tm)), "r"(bar), "r"(c0), "r"(c1)
        : "memory");
}
__device__ __forceinline__ void wg_fence() { asm volatile("wgmma.fence.sync.aligned;\n" ::: "memory"); }
__device__ __forceinline__ void wg_commit() { asm volatile("wgmma.commit_group.sync.aligned;\n" ::: "memory"); }
template <int N>
__device__ __forceinline__ void wg_wait() { asm volatile("wgmma.wait_group.sync.aligned %0;\n" ::"n"(N) : "memory"); }
__device__ __forceinline__ void wg_bar(int id) { asm volatile("bar.sync %0, 128;" ::"r"(id) : "memory"); }
__device__ __forceinline__ void proxy_fence() {
 asm volatile("fence.proxy.async.shared::cta;\n" ::: "memory"); }
__device__ __forceinline__ void cp_async16(uint32_t dst, const void* src) {
    asm volatile("cp.async.cg.shared.global [%0], [%1], 16;\n" ::"r"(dst), "l"(src) : "memory");
}
__device__ __forceinline__ void cp_async_commit() { asm volatile("cp.async.commit_group;\n" ::: "memory"); }
__device__ __forceinline__ void cp_async_wait_all() { asm volatile("cp.async.wait_group 0;\n" ::: "memory"); }
__device__ __forceinline__ void prefetch_l2(const void* p) { asm volatile("prefetch.global.L2 [%0];\n" ::"l"(p)); }

__device__ __forceinline__ float tanh_approx(float x) {
    float y;
    asm("tanh.approx.f32 %0, %1;" : "=f"(y) : "f"(x));
    return y;
}
__device__ __forceinline__ uint32_t pack_bf16(float lo, float hi) {
    uint32_t r;
    asm("cvt.rn.bf16x2.f32 %0, %1, %2;" : "=r"(r) : "f"(hi), "f"(lo));
    return r;
}
__device__ __forceinline__ float bf_lo(uint32_t v) { return __uint_as_float(v << 16); }
__device__ __forceinline__ float bf_hi(uint32_t v) { return __uint_as_float(v & 0xffff0000u); }

#define ACC32(d)                                                                                             \
    "+f"(d[0]), "+f"(d[1]), "+f"(d[2]), "+f"(d[3]), "+f"(d[4]), "+f"(d[5]), "+f"(d[6]), "+f"(d[7]),          \
        "+f"(d[8]), "+f"(d[9]), "+f"(d[10]), "+f"(d[11]), "+f"(d[12]), "+f"(d[13]), "+f"(d[14]), "+f"(d[15]), \
        "+f"(d[16]), "+f"(d[17]), "+f"(d[18]), "+f"(d[19]), "+f"(d[20]), "+f"(d[21]), "+f"(d[22]),           \
        "+f"(d[23]), "+f"(d[24]), "+f"(d[25]), "+f"(d[26]), "+f"(d[27]), "+f"(d[28]), "+f"(d[29]),           \
        "+f"(d[30]), "+f"(d[31])
#define ACC32_STR                                                                \
    "{%0, %1, %2, %3, %4, %5, %6, %7, %8, %9, %10, %11, %12, %13, %14, %15, "    \
    " %16, %17, %18, %19, %20, %21, %22, %23, %24, %25, %26, %27, %28, %29, %30, %31}"

__device__ __forceinline__ void wgmma_ss_n64_tA(float (&d)[32], uint64_t adesc, uint64_t bdesc, int scale_d) {
    asm volatile(
        "{\n.reg .pred p;\nsetp.ne.b32 p, %34, 0;\n"
        "wgmma.mma_async.sync.aligned.m64n64k16.f32.bf16.bf16 " ACC32_STR ", %32, %33, p, 1, 1, 1, 0;\n}\n"
        : ACC32(d)
        : "l"(adesc), "l"(bdesc), "r"(scale_d));
}
__device__ __forceinline__ void wgmma_ss_n64(float (&d)[32], uint64_t adesc, uint64_t bdesc, int scale_d) {
    asm volatile(
        "{\n.reg .pred p;\nsetp.ne.b32 p, %34, 0;\n"
        "wgmma.mma_async.sync.aligned.m64n64k16.f32.bf16.bf16 " ACC32_STR ", %32, %33, p, 1, 1, 0, 1;\n}\n"
        : ACC32(d)
        : "l"(adesc), "l"(bdesc), "r"(scale_d));
}
__device__ __forceinline__ void wgmma_n96(float (&d)[48], uint32_t a0, uint32_t a1, uint32_t a2, uint32_t a3,
                                          uint64_t bdesc) {
    asm volatile(
        "{\n"
        "wgmma.mma_async.sync.aligned.m64n96k16.f32.bf16.bf16 "
        "{%0, %1, %2, %3, %4, %5, %6, %7, %8, %9, %10, %11, %12, %13, %14, %15, "
        " %16, %17, %18, %19, %20, %21, %22, %23, %24, %25, %26, %27, %28, %29, %30, %31, "
        " %32, %33, %34, %35, %36, %37, %38, %39, %40, %41, %42, %43, %44, %45, %46, %47}, "
        "{%48, %49, %50, %51}, %52, 1, 1, 1, 1;\n"
        "}\n"
        : ACC32(d), "+f"(d[32]), "+f"(d[33]), "+f"(d[34]), "+f"(d[35]), "+f"(d[36]), "+f"(d[37]), "+f"(d[38]),
          "+f"(d[39]), "+f"(d[40]), "+f"(d[41]), "+f"(d[42]), "+f"(d[43]), "+f"(d[44]), "+f"(d[45]), "+f"(d[46]),
          "+f"(d[47])
        : "r"(a0), "r"(a1), "r"(a2), "r"(a3), "l"(bdesc));
}

#define W2_LBO 128
#define W2_SBO (48 * 128)
#define W1_BOX_BYTES (96 * 128)
#define Y_BOX_BYTES (64 * 64)
#define Y_TILE_BYTES (3 * Y_BOX_BYTES)

__device__ __forceinline__ void ln_row4(const uint4 (&xv)[3], const float* __restrict__ s_dwq, uint4 (&y)[3]) {
    float xf[24], dwf[24];
    float s = 0.f;
#pragma unroll
    for (int i = 0; i < 3; i++) {
        uint32_t w[4] = {xv[i].x, xv[i].y, xv[i].z, xv[i].w};
        float4 da = *reinterpret_cast<const float4*>(s_dwq + 32 * i);
        float4 db = *reinterpret_cast<const float4*>(s_dwq + 32 * i + 4);
        dwf[i * 8 + 0] = da.x; dwf[i * 8 + 1] = da.y; dwf[i * 8 + 2] = da.z; dwf[i * 8 + 3] = da.w;
        dwf[i * 8 + 4] = db.x; dwf[i * 8 + 5] = db.y; dwf[i * 8 + 6] = db.z; dwf[i * 8 + 7] = db.w;
#pragma unroll
        for (int p = 0; p < 4; p++) {
            xf[i * 8 + 2 * p] = bf_lo(w[p]);
            xf[i * 8 + 2 * p + 1] = bf_hi(w[p]);
        }
#pragma unroll
        for (int p = 0; p < 8; p++) s = fmaf(xf[i * 8 + p], dwf[i * 8 + p], s);
    }
    s += __shfl_xor_sync(0xffffffffu, s, 1);
    s += __shfl_xor_sync(0xffffffffu, s, 2);
    float nmean = s * (-1.0f / C_IN);
    float v = 0.f;
#pragma unroll
    for (int i = 0; i < 24; i++) {
        xf[i] = fmaf(xf[i], dwf[i], nmean);
        v = fmaf(xf[i], xf[i], v);
    }
    v += __shfl_xor_sync(0xffffffffu, v, 1);
    v += __shfl_xor_sync(0xffffffffu, v, 2);
    float rstd = rsqrtf(v * (1.0f / C_IN) + 1e-5f) * GELU_KAPPA;
#pragma unroll
    for (int i = 0; i < 3; i++) {
        y[i].x = pack_bf16(xf[i * 8 + 0] * rstd, xf[i * 8 + 1] * rstd);
        y[i].y = pack_bf16(xf[i * 8 + 2] * rstd, xf[i * 8 + 3] * rstd);
        y[i].z = pack_bf16(xf[i * 8 + 4] * rstd, xf[i * 8 + 5] * rstd);
        y[i].w = pack_bf16(xf[i * 8 + 6] * rstd, xf[i * 8 + 7] * rstd);
    }
}

__device__ __forceinline__ void ln_tile_inplace(unsigned char* yp, const float* __restrict__ s_dwq) {
    uint4 xv[3], y[3];
#pragma unroll
    for (int i = 0; i < 3; i++) xv[i] = *reinterpret_cast<const uint4*>(yp + i * Y_BOX_BYTES);
    ln_row4(xv, s_dwq, y);
#pragma unroll
    for (int i = 0; i < 3; i++) *reinterpret_cast<uint4*>(yp + i * Y_BOX_BYTES) = y[i];
#pragma unroll
    for (int i = 0; i < 3; i++) xv[i] = *reinterpret_cast<const uint4*>(yp + 512 + i * Y_BOX_BYTES);
    ln_row4(xv, s_dwq, y);
#pragma unroll
    for (int i = 0; i < 3; i++) *reinterpret_cast<uint4*>(yp + 512 + i * Y_BOX_BYTES) = y[i];
}

__device__ __forceinline__ float gelu2(float u) {
    float t = fmaf(u, u, GELU_C0K);
    float a = t * u;
    float th = tanh_approx(a);
    return fmaf(u, th, u);
}

__device__ __forceinline__ void tma_x_tile(uint32_t dst, const CUtensorMap* tmx, uint32_t bar, int tile) {
    mbar_expect_tx(bar, Y_TILE_BYTES);
#pragma unroll
    for (int i = 0; i < 3; i++) tma_load_2d(dst + i * Y_BOX_BYTES, tmx, bar, i * 32, tile * TILE_M);
}

__global__ void __launch_bounds__(NTHR, 1)
k_stats(const __grid_constant__ CUtensorMap tm_x, const __grid_constant__ CUtensorMap tm_w1,
        const __nv_bfloat16* __restrict__ dw) {
    extern __shared__ __align__(1024) unsigned char smem[];
    unsigned char* s_w1 = smem;
    unsigned char* s_y = smem + 73728;
    float* s_dw = reinterpret_cast<float*>(smem + 73728 + NWG * 2 * Y_TILE_BYTES);
    float* s_red = s_dw + 128;
    uint64_t* s_bar = reinterpret_cast<uint64_t*>(s_red + C_H);

    const int tid = threadIdx.x;
    const int wg = tid >> 7;
    const int warp = (tid >> 5) & 3;
    const int lane = tid & 31;
    const int q = lane & 3;
    const int nwg = gridDim.x * NWG;
    int tile = blockIdx.x * NWG + wg;

    if (tid == 0) {
        for (int i = 0; i < 1 + 2 * NWG; i++) mbar_init(smem_u32(s_bar + i), 1);
        asm volatile("fence.mbarrier_init.release.cluster;\n" ::: "memory");
    }
    if (tid < C_IN) s_dw[tid] = __bfloat162float(dw[tid]);
    for (int i = tid; i < C_H; i += NTHR) s_red[i] = 0.f;
    __syncthreads();
    const uint32_t ybuf0 = smem_u32(s_y + wg * 2 * Y_TILE_BYTES);
    const uint32_t bar_y = smem_u32(s_bar + 1 + 2 * wg);
    if (tid == 0) {
        mbar_expect_tx(smem_u32(s_bar), 6 * W1_BOX_BYTES);
        for (int i = 0; i < 6; i++) tma_load_2d(smem_u32(s_w1) + i * W1_BOX_BYTES, &tm_w1, smem_u32(s_bar), i * 64, 0);
    }
    if ((tid & 127) == 0 && tile < NTILES) tma_x_tile(ybuf0, &tm_x, bar_y, tile);

    asm volatile("griddepcontrol.launch_dependents;\n" ::: "memory");
    float ss[12];
#pragma unroll
    for (int i = 0; i < 12; i++) ss[i] = 0.f;

    const uint64_t w1_desc = make_desc(smem_u32(s_w1), W1_BOX_BYTES, 1024, 1);
    const int rl = warp * 16 + (lane >> 2);
    const int yoff = rl * 64 + ((q ^ ((rl >> 1) & 3)) * 16);
    mbar_wait(smem_u32(s_bar), 0);

    int it = 0;
    for (; tile < NTILES; tile += nwg, it++) {
        const int buf = it & 1;
        if ((tid & 127) == 0 && tile + nwg < NTILES) tma_x_tile(ybuf0 + (buf ^ 1) * Y_TILE_BYTES, &tm_x, bar_y + (buf ^ 1) * 8, tile + nwg);
        mbar_wait(bar_y + buf * 8, (it >> 1) & 1);
        unsigned char* ytile = s_y + (wg * 2 + buf) * Y_TILE_BYTES;
        ln_tile_inplace(ytile + yoff, s_dw + 8 * q);
        proxy_fence();
        wg_bar(1 + wg);
        const uint64_t y_desc = make_desc(smem_u32(ytile), 16, 512, 2);
        float S[2][32];
        wg_fence();
#pragma unroll
        for (int t = 0; t < 6; t++)
            wgmma_ss_n64_tA(S[0], w1_desc + ((t * 2048) >> 4), y_desc + (((t >> 1) * Y_BOX_BYTES + (t & 1) * 32) >> 4), t != 0);
        wg_commit();
#pragma unroll
        for (int m = 0; m < 6; m++) {
            if (m + 1 < 6) {
                wg_fence();
#pragma unroll
                for (int t = 0; t < 6; t++)
                    wgmma_ss_n64_tA(S[(m + 1) & 1], w1_desc + (((m + 1) * W1_BOX_BYTES + t * 2048) >> 4),
                                    y_desc + (((t >> 1) * Y_BOX_BYTES + (t & 1) * 32) >> 4), t != 0);
                wg_commit();
                wg_wait<1>();
            } else {
                wg_wait<0>();
            }
            float(&Sc)[32] = S[m & 1];
            float a0 = ss[2 * m], a1 = ss[2 * m + 1];
#pragma unroll
            for (int j = 0; j < 8; j++) {
                float g0 = gelu2(Sc[4 * j]);
                float g1 = gelu2(Sc[4 * j + 1]);
                float g2 = gelu2(Sc[4 * j + 2]);
                float g3 = gelu2(Sc[4 * j + 3]);
                a0 = fmaf(g0, g0, a0);
                a1 = fmaf(g2, g2, a1);
                a0 = fmaf(g1, g1, a0);
                a1 = fmaf(g3, g3, a1);
            }
            ss[2 * m] = a0;
            ss[2 * m + 1] = a1;
        }
        wg_bar(1 + wg);
    }
#pragma unroll
    for (int i = 0; i < 12; i++) {
        float v = ss[i];
        v += __shfl_xor_sync(0xffffffffu, v, 1);
        v += __shfl_xor_sync(0xffffffffu, v, 2);
        if (q == 0) {
            int m = i >> 1, hh = i & 1;
            atomicAdd(&s_red[m * 64 + warp * 16 + hh * 8 + (lane >> 2)], v);
        }
    }
    __syncthreads();
    const float sc = 0.25f / (GELU_KAPPA * GELU_KAPPA);
    for (int i = tid; i < C_H; i += NTHR) atomicAdd(&g_sum[i], s_red[i] * sc);
}

#define NWG2 2
#define NTHR2 (NWG2 * 128)

__device__ __forceinline__ void wgmma_rs_n64(float (&d)[32], uint32_t a0, uint32_t a1, uint32_t a2, uint32_t a3,
                                             uint64_t bdesc, int scale_d) {
    asm volatile(
        "{\n.reg .pred p;\nsetp.ne.b32 p, %37, 0;\n"
        "wgmma.mma_async.sync.aligned.m64n64k16.f32.bf16.bf16 " ACC32_STR ", {%32, %33, %34, %35}, %36, p, 1, 1, 1;\n}\n"
        : ACC32(d)
        : "r"(a0), "r"(a1), "r"(a2), "r"(a3), "l"(bdesc), "r"(scale_d));
}
__device__ __forceinline__ void ldsm_x4(uint32_t addr, uint32_t& r0, uint32_t& r1, uint32_t& r2, uint32_t& r3) {
    asm volatile("ldmatrix.sync.aligned.m8n8.x4.shared.b16 {%0, %1, %2, %3}, [%4];\n"
                 : "=r"(r0), "=r"(r1), "=r"(r2), "=r"(r3) : "r"(addr) : "memory");
}
__device__ __forceinline__ void stsm_x4(uint32_t addr, uint32_t r0, uint32_t r1, uint32_t r2, uint32_t r3) {
    asm volatile("stmatrix.sync.aligned.m8n8.x4.shared.b16 [%0], {%1, %2, %3, %4};\n" ::"r"(addr), "r"(r0), "r"(r1), "r"(r2),
                 "r"(r3) : "memory");
}
__device__ __forceinline__ void tma_store_2d(const CUtensorMap* tm, uint32_t src, int c0, int c1) {
    asm volatile("cp.async.bulk.tensor.2d.global.shared::cta.bulk_group [%0, {%2, %3}], [%1];\n" ::"l"(
                     reinterpret_cast<uint64_t>(tm)), "r"(src), "r"(c0), "r"(c1) : "memory");
}

__device__ __forceinline__ void ln_frag(uint32_t (&f)[6][4], const float* __restrict__ s_dwq) {
    float xa[24], xb[24], dwf[24];
    float sa = 0.f, sb = 0.f;
#pragma unroll
    for (int t = 0; t < 6; t++) {
#pragma unroll
        for (int h = 0; h < 2; h++) {
            float2 d = *reinterpret_cast<const float2*>(s_dwq + 16 * t + 8 * h);
            int i = t * 4 + h * 2;
            dwf[i] = d.x; dwf[i + 1] = d.y;
            xa[i] = bf_lo(f[t][2 * h]); xa[i + 1] = bf_hi(f[t][2 * h]);
            xb[i] = bf_lo(f[t][2 * h + 1]); xb[i + 1] = bf_hi(f[t][2 * h + 1]);
            sa = fmaf(xa[i], d.x, sa); sa = fmaf(xa[i + 1], d.y, sa);
            sb = fmaf(xb[i], d.x, sb); sb = fmaf(xb[i + 1], d.y, sb);
        }
    }
    sa += __shfl_xor_sync(0xffffffffu, sa, 1);
    sb += __shfl_xor_sync(0xffffffffu, sb, 1);
    sa += __shfl_xor_sync(0xffffffffu, sa, 2);
    sb += __shfl_xor_sync(0xffffffffu, sb, 2);
    float ma = sa * (-1.0f / C_IN), mb = sb * (-1.0f / C_IN);
    float va = 0.f, vb = 0.f;
#pragma unroll
    for (int i = 0; i < 24; i++) {
        xa[i] = fmaf(xa[i], dwf[i], ma);
        xb[i] = fmaf(xb[i], dwf[i], mb);
        va = fmaf(xa[i], xa[i], va);
        vb = fmaf(xb[i], xb[i], vb);
    }
    va += __shfl_xor_sync(0xffffffffu, va, 1);
    vb += __shfl_xor_sync(0xffffffffu, vb, 1);
    va += __shfl_xor_sync(0xffffffffu, va, 2);
    vb += __shfl_xor_sync(0xffffffffu, vb, 2);
    float ra = rsqrtf(va * (1.0f / C_IN) + 1e-5f) * GELU_KAPPA;
    float rb = rsqrtf(vb * (1.0f / C_IN) + 1e-5f) * GELU_KAPPA;
#pragma unroll
    for (int t = 0; t < 6; t++) {
#pragma unroll
        for (int h = 0; h < 2; h++) {
            int i = t * 4 + h * 2;
            f[t][2 * h] = pack_bf16(xa[i] * ra, xa[i + 1] * ra);
            f[t][2 * h + 1] = pack_bf16(xb[i] * rb, xb[i + 1] * rb);
        }
    }
}

__global__ void __launch_bounds__(NTHR2, 1)
k_main(const __grid_constant__ CUtensorMap tm_x, const __grid_constant__ CUtensorMap tm_w1,
       const __grid_constant__ CUtensorMap tm_out, const __nv_bfloat16* __restrict__ dw,
       const __nv_bfloat16* __restrict__ w2, const __nv_bfloat16* __restrict__ grn_g,
       const __nv_bfloat16* __restrict__ grn_b) {
    extern __shared__ __align__(1024) unsigned char smem[];
    unsigned char* s_w1 = smem;
    unsigned char* s_w2 = smem + 73728;
    unsigned char* s_x = smem + 2 * 73728;
    float* s_dw = reinterpret_cast<float*>(smem + 2 * 73728 + NWG2 * 2 * Y_TILE_BYTES);
    float* s_c = s_dw + 128;
    float* s_s = s_c + 128;
    float* s_tmp = s_s + C_H;
    uint64_t* s_bar = reinterpret_cast<uint64_t*>(s_tmp + 16);

    const int tid = threadIdx.x;
    const int wg = tid >> 7;
    const int warp = (tid >> 5) & 3;
    const int lane = tid & 31;
    const int q = lane & 3;
    const int nwg = gridDim.x * NWG2;
    int tile = blockIdx.x * NWG2 + wg;

    const uint32_t xbuf0 = smem_u32(s_x + wg * 2 * Y_TILE_BYTES);
    const uint32_t bar_x = smem_u32(s_bar + 1 + 2 * wg);
    if (tid == 0) {
        for (int i = 0; i < 1 + 2 * NWG2; i++) mbar_init(smem_u32(s_bar + i), 1);
        asm volatile("fence.mbarrier_init.release.cluster;\n" ::: "memory");
    }
    if (tid < C_IN) { s_dw[tid] = __bfloat162float(dw[tid]); s_c[tid] = 0.f; }
    __syncthreads();
    if (tid == 0) {
        mbar_expect_tx(smem_u32(s_bar), 6 * W1_BOX_BYTES);
        for (int i = 0; i < 6; i++) tma_load_2d(smem_u32(s_w1) + i * W1_BOX_BYTES, &tm_w1, smem_u32(s_bar), i * 64, 0);
    }
    if ((tid & 127) == 0 && tile < NTILES) tma_x_tile(xbuf0, &tm_x, bar_x, tile);
    constexpr int W2_ITEMS = 384 * 12 / NTHR2;
    uint4 w2v[W2_ITEMS];
#pragma unroll
    for (int i = 0; i < W2_ITEMS; i++) {
        int it2 = tid + i * NTHR2;
        int kr = it2 & 7;
        int nb = (it2 >> 3) % 12;
        int kb = (it2 >> 3) / 12;
        w2v[i] = __ldg(reinterpret_cast<const uint4*>(w2 + (kb * 8 + kr) * C_IN + nb * 8));
    }
    {
        float a0 = 0.f, a1 = 0.f, a2 = 0.f;
        constexpr int KPW = C_H / (NTHR2 / 32);
        int kbase = (tid >> 5) * KPW;
#pragma unroll 8
        for (int k = kbase; k < kbase + KPW; k++) {
            float b = __bfloat162float(grn_b[k]);
            a0 = fmaf(b, __bfloat162float(w2[k * C_IN + lane]), a0);
            a1 = fmaf(b, __bfloat162float(w2[k * C_IN + lane + 32]), a1);
            a2 = fmaf(b, __bfloat162float(w2[k * C_IN + lane + 64]), a2);
        }
        atomicAdd(&s_c[lane], a0);
        atomicAdd(&s_c[lane + 32], a1);
        atomicAdd(&s_c[lane + 64], a2);
    }
    float gg[2];
    gg[0] = __bfloat162float(grn_g[tid]);
    gg[1] = (tid + NTHR2 < C_H) ? __bfloat162float(grn_g[tid + NTHR2]) : 0.f;
    asm volatile("griddepcontrol.wait;\n" ::: "memory");
    float lsum = 0.f;
    for (int k = tid; k < C_H; k += NTHR2) {
        float gx = sqrtf(__ldcg(&g_sum[k]) + 1e-6f);
        s_s[k] = gx;
        lsum += gx;
    }
#pragma unroll
    for (int o = 16; o > 0; o >>= 1) lsum += __shfl_xor_sync(0xffffffffu, lsum, o);
    if (lane == 0) s_tmp[tid >> 5] = lsum;
    __syncthreads();
    __shared__ unsigned int s_last;
    if (tid == 0) s_last = (atomicAdd(&g_done, 1u) == gridDim.x - 1);
    float tot = 0.f;
#pragma unroll
    for (int i = 0; i < NTHR2 / 32; i++) tot += s_tmp[i];
    float inv = 1.0f / (tot * (1.0f / C_H) + 1e-6f);
    {
        int j = 0;
        for (int k = tid; k < C_H; k += NTHR2, j++) s_s[k] = (0.5f / GELU_KAPPA) * (1.0f + gg[j] * (s_s[k] * inv));
    }
    __syncthreads();
    if (s_last) {
        for (int k = tid; k < C_H; k += NTHR2) g_sum[k] = 0.f;
        if (tid == 0) g_done = 0;
    }
#pragma unroll
    for (int i = 0; i < W2_ITEMS; i++) {
        int it2 = tid + i * NTHR2;
        int kr = it2 & 7;
        int nb = (it2 >> 3) % 12;
        int kb = (it2 >> 3) / 12;
        float sk = s_s[kb * 8 + kr];
        uint4 v = w2v[i];
        uint4 o;
        o.x = pack_bf16(sk * bf_lo(v.x), sk * bf_hi(v.x));
        o.y = pack_bf16(sk * bf_lo(v.y), sk * bf_hi(v.y));
        o.z = pack_bf16(sk * bf_lo(v.z), sk * bf_hi(v.z));
        o.w = pack_bf16(sk * bf_lo(v.w), sk * bf_hi(v.w));
        *reinterpret_cast<uint4*>(s_w2 + nb * W2_SBO + kb * W2_LBO + kr * 16) = o;
    }
    proxy_fence();
    __syncthreads();
    mbar_wait(smem_u32(s_bar), 0);

    const uint64_t w1_desc = make_desc(smem_u32(s_w1), W1_BOX_BYTES, 1024, 1);
    const uint64_t w2_desc = make_desc(smem_u32(s_w2), W2_LBO, W2_SBO, 0);
    const int lrow = warp * 16 + ((lane >> 3) & 1) * 8 + (lane & 7);
    const int lhalf = lane >> 4;
    const int lsw = (lrow >> 1) & 3;
    const uint32_t loff0 = lrow * 64 + (((0 + lhalf) ^ lsw) << 4);
    const uint32_t loff1 = lrow * 64 + (((2 + lhalf) ^ lsw) << 4);

    int it = 0;
    for (; tile < NTILES; tile += nwg, it++) {
        const int buf = it & 1;
        const uint32_t xb = xbuf0 + buf * Y_TILE_BYTES;
        if ((tid & 127) == 0 && tile + nwg < NTILES) {
            asm volatile("cp.async.bulk.wait_group.read 0;\n" ::: "memory");
            tma_x_tile(xbuf0 + (buf ^ 1) * Y_TILE_BYTES, &tm_x, bar_x + (buf ^ 1) * 8, tile + nwg);
        }
        mbar_wait(bar_x + buf * 8, (it >> 1) & 1);
        uint32_t f[6][4];
#pragma unroll
        for (int t = 0; t < 6; t++)
            ldsm_x4(xb + (t >> 1) * Y_BOX_BYTES + ((t & 1) ? loff1 : loff0), f[t][0], f[t][1], f[t][2], f[t][3]);
        ln_frag(f, s_dw + 2 * q);

        float O[48];
#pragma unroll
        for (int j = 0; j < 12; j++) {
            float2 cc = *reinterpret_cast<const float2*>(&s_c[8 * j + 2 * q]);
            O[4 * j] = cc.x; O[4 * j + 1] = cc.y; O[4 * j + 2] = cc.x; O[4 * j + 3] = cc.y;
        }
        float S[2][32];
        uint32_t hf[2][16];
        wg_fence();
#pragma unroll
        for (int t = 0; t < 6; t++) wgmma_rs_n64(S[0], f[t][0], f[t][1], f[t][2], f[t][3], w1_desc + ((t * 2048) >> 4), t != 0);
        wg_commit();
#pragma unroll
        for (int c = 0; c < 6; c++) {
            if (c + 1 < 6) {
                wg_fence();
#pragma unroll
                for (int t = 0; t < 6; t++)
                    wgmma_rs_n64(S[(c + 1) & 1], f[t][0], f[t][1], f[t][2], f[t][3],
                                 w1_desc + (((c + 1) * W1_BOX_BYTES + t * 2048) >> 4), t != 0);
                wg_commit();
                if (c == 0) wg_wait<1>(); else wg_wait<2>();
            } else {
                wg_wait<1>();
            }
            float(&Sc)[32] = S[c & 1];
            uint32_t(&h)[16] = hf[c & 1];
#pragma unroll
            for (int j = 0; j < 8; j++) {
                float g0 = gelu2(Sc[4 * j]);
                float g1 = gelu2(Sc[4 * j + 1]);
                float g2 = gelu2(Sc[4 * j + 2]);
                float g3 = gelu2(Sc[4 * j + 3]);
                h[2 * j] = pack_bf16(g0, g1);
                h[2 * j + 1] = pack_bf16(g2, g3);
            }
            wg_fence();
#pragma unroll
            for (int t = 0; t < 4; t++)
                wgmma_n96(O, h[4 * t], h[4 * t + 1], h[4 * t + 2], h[4 * t + 3],
                          w2_desc + (((c * 8 + 2 * t) * W2_LBO) >> 4));
            wg_commit();
        }
        uint32_t xr[6][4];
#pragma unroll
        for (int t = 0; t < 6; t++)
            ldsm_x4(xb + (t >> 1) * Y_BOX_BYTES + ((t & 1) ? loff1 : loff0), xr[t][0], xr[t][1], xr[t][2], xr[t][3]);
        wg_wait<0>();
#pragma unroll
        for (int t = 0; t < 6; t++) {
            uint32_t o0 = pack_bf16(bf_lo(xr[t][0]) + O[8 * t + 0], bf_hi(xr[t][0]) + O[8 * t + 1]);
            uint32_t o1 = pack_bf16(bf_lo(xr[t][1]) + O[8 * t + 2], bf_hi(xr[t][1]) + O[8 * t + 3]);
            uint32_t o2 = pack_bf16(bf_lo(xr[t][2]) + O[8 * t + 4], bf_hi(xr[t][2]) + O[8 * t + 5]);
            uint32_t o3 = pack_bf16(bf_lo(xr[t][3]) + O[8 * t + 6], bf_hi(xr[t][3]) + O[8 * t + 7]);
            stsm_x4(xb + (t >> 1) * Y_BOX_BYTES + ((t & 1) ? loff1 : loff0), o0, o1, o2, o3);
        }
        proxy_fence();
        wg_bar(1 + wg);
        if ((tid & 127) == 0) {
#pragma unroll
            for (int i = 0; i < 3; i++) tma_store_2d(&tm_out, xb + i * Y_BOX_BYTES, i * 32, tile * TILE_M);
            asm volatile("cp.async.bulk.commit_group;\n" ::: "memory");
        }
    }
    if ((tid & 127) == 0) asm volatile("cp.async.bulk.wait_group 0;\n" ::: "memory");
}

#define SMEM1 (73728 + NWG * 2 * Y_TILE_BYTES + 512 + 1536 + 128)
#define SMEM2 (2 * 73728 + NWG2 * 2 * Y_TILE_BYTES + 512 + 512 + 1536 + 64 + 64)

typedef CUresult (*PFN_encodeTiled)(CUtensorMap*, CUtensorMapDataType, cuuint32_t, void*, const cuuint64_t*, const cuuint64_t*,
                                    const cuuint32_t*, const cuuint32_t*, CUtensorMapInterleave, CUtensorMapSwizzle,
                                    CUtensorMapL2promotion, CUtensorMapFloatOOBfill);

extern "C" void kernel_launch(void* const* d_in, const int* in_sizes, int n_in, void* d_out, int out_size) {
    const __nv_bfloat16* x = (const __nv_bfloat16*)d_in[0];
    const __nv_bfloat16* dw = (const __nv_bfloat16*)d_in[1];
    const __nv_bfloat16* w1 = (const __nv_bfloat16*)d_in[2];
    const __nv_bfloat16* w2 = (const __nv_bfloat16*)d_in[3];
    const __nv_bfloat16* grn_g = (const __nv_bfloat16*)d_in[4];
    const __nv_bfloat16* grn_b = (const __nv_bfloat16*)d_in[5];

    static int n_sm = 0;
    static CUtensorMap tm_x, tm_w1, tm_out;
    static const void* last_x = nullptr;
    static const void* last_w1 = nullptr;
    static const void* last_out = nullptr;
    static PFN_encodeTiled encode = nullptr;
    if (n_sm == 0) {
        int dev = 0;
        cudaGetDevice(&dev);
        cudaDeviceGetAttribute(&n_sm, cudaDevAttrMultiProcessorCount, dev);
        if (n_sm > MAX_CTAS) n_sm = MAX_CTAS;
        cudaFuncSetAttribute(k_stats, cudaFuncAttributeMaxDynamicSharedMemorySize, SMEM1);
        cudaFuncSetAttribute(k_main, cudaFuncAttributeMaxDynamicSharedMemorySize, SMEM2);
        cudaDriverEntryPointQueryResult qres;
        void* fn = nullptr;
        cudaGetDriverEntryPoint("cuTensorMapEncodeTiled", &fn, cudaEnableDefault, &qres);
        encode = (PFN_encodeTiled)fn;
    }
    if (last_x != x || last_w1 != w1 || last_out != d_out) {
        cuuint64_t dims[2] = {96, (cuuint64_t)NROWS};
        cuuint64_t strides[1] = {192};
        cuuint32_t box[2] = {32, 64};
        cuuint32_t es[2] = {1, 1};
        encode(&tm_x, CU_TENSOR_MAP_DATA_TYPE_BFLOAT16, 2, (void*)x, dims, strides, box, es, CU_TENSOR_MAP_INTERLEAVE_NONE,
               CU_TENSOR_MAP_SWIZZLE_64B, CU_TENSOR_MAP_L2_PROMOTION_L2_128B, CU_TENSOR_MAP_FLOAT_OOB_FILL_NONE);
        encode(&tm_out, CU_TENSOR_MAP_DATA_TYPE_BFLOAT16, 2, d_out, dims, strides, box, es, CU_TENSOR_MAP_INTERLEAVE_NONE,
               CU_TENSOR_MAP_SWIZZLE_64B, CU_TENSOR_MAP_L2_PROMOTION_L2_128B, CU_TENSOR_MAP_FLOAT_OOB_FILL_NONE);
        cuuint64_t dimsw[2] = {384, 96};
        cuuint64_t stridesw[1] = {768};
        cuuint32_t boxw[2] = {64, 96};
        encode(&tm_w1, CU_TENSOR_MAP_DATA_TYPE_BFLOAT16, 2, (void*)w1, dimsw, stridesw, boxw, es, CU_TENSOR_MAP_INTERLEAVE_NONE,
               CU_TENSOR_MAP_SWIZZLE_128B, CU_TENSOR_MAP_L2_PROMOTION_L2_128B, CU_TENSOR_MAP_FLOAT_OOB_FILL_NONE);
        last_x = x;
        last_w1 = w1;
        last_out = d_out;
    }
    k_stats<<<n_sm, NTHR, SMEM1>>>(tm_x, tm_w1, dw);
    cudaLaunchConfig_t cfg = {};
    cfg.gridDim = dim3(n_sm);
    cfg.blockDim = dim3(NTHR2);
    cfg.dynamicSmemBytes = SMEM2;
    cfg.stream = cudaStreamPerThread;
    cudaLaunchAttribute attr[1];
    attr[0].id = cudaLaunchAttributeProgrammaticStreamSerialization;
    attr[0].val.programmaticStreamSerializationAllowed = 1;
    cfg.attrs = attr;
    cfg.numAttrs = 1;
    cudaLaunchKernelEx(&cfg, k_main, tm_x, tm_w1, tm_out, dw, w2, grn_g, grn_b);
}
```

```cpp
#include <cuda_runtime.h>
#include <cuda_bf16.h>
#include <stdint.h>
#include <cuda.h>

#define C_IN 96
#define C_H 384
#define NROWS (512 * 512)
#define TILE_M 64
#define NTILES (NROWS / TILE_M)
#define MAX_CTAS 256
#define NWG 4
#define NTHR (NWG * 128)

__device__ float g_sum[C_H];
__device__ unsigned int g_done;

#define TSTAMP(i)

#define GELU_KAPPA 0.3292034911525734f
#define GELU_C0K 2.423681954311584f

__device__ __forceinline__ uint32_t smem_u32(const void* p) { return (uint32_t)__cvta_generic_to_shared(p); }
__device__ __forceinline__ uint64_t make_desc(uint32_t addr, uint32_t lbo, uint32_t sbo, uint32_t swz = 0) {
    uint64_t d = 0;
    d |= (uint64_t)((addr & 0x3FFFF) >> 4);
    d |= (uint64_t)((lbo >> 4) & 0x3FFF) << 16;
    d |= (uint64_t)((sbo >> 4) & 0x3FFF) << 32;
    d |= (uint64_t)swz << 62;
    return d;
}
__device__ __forceinline__ void mbar_init(uint32_t bar, uint32_t count) {
    asm volatile("mbarrier.init.shared::cta.b64 [%0], %1;\n" ::"r"(bar), "r"(count) : "memory");
}
__device__ __forceinline__ void mbar_expect_tx(uint32_t bar, uint32_t bytes) {
    asm volatile("mbarrier.arrive.expect_tx.shared::cta.b64 _, [%0], %1;\n" ::"r"(bar), "r"(bytes) : "memory");
}
__device__ __forceinline__ void mbar_wait(uint32_t bar, uint32_t parity) {
    asm volatile(
        "{\n.reg .pred p;\n"
        "WAIT_LOOP:\n"
        "mbarrier.try_wait.parity.shared::cta.b64 p, [%0], %1;\n"
        "@p bra WAIT_DONE;\n"
        "bra WAIT_LOOP;\n"
        "WAIT_DONE:\n}\n" ::"r"(bar), "r"(parity) : "memory");
}
__device__ __forceinline__ void tma_load_2d(uint32_t dst, const CUtensorMap* tm, uint32_t bar, int c0, int c1) {
    asm volatile(
        "cp.async.bulk.tensor.2d.shared::cluster.global.mbarrier::complete_tx::bytes [%0], [%1, {%3, %4}], [%2];\n" ::"r"(dst),
        "l"(reinterpret_cast<uint64_t>(tm)), "r"(bar), "r"(c0), "r"(c1)
        : "memory");
}
__device__ __forceinline__ void wg_fence() { asm volatile("wgmma.fence.sync.aligned;\n" ::: "memory"); }
__device__ __forceinline__ void wg_commit() { asm volatile("wgmma.commit_group.sync.aligned;\n" ::: "memory"); }
template <int N>
__device__ __forceinline__ void wg_wait() { asm volatile("wgmma.wait_group.sync.aligned %0;\n" ::"n"(N) : "memory"); }
__device__ __forceinline__ void wg_bar(int id) { asm volatile("bar.sync %0, 128;" ::"r"(id) : "memory"); }
__device__ __forceinline__ void proxy_fence() {
 asm volatile("fence.proxy.async.shared::cta;\n" ::: "memory"); }
__device__ __forceinline__ void cp_async16(uint32_t dst, const void* src) {
    asm volatile("cp.async.cg.shared.global [%0], [%1], 16;\n" ::"r"(dst), "l"(src) : "memory");
}
__device__ __forceinline__ void cp_async_commit() { asm volatile("cp.async.commit_group;\n" ::: "memory"); }
__device__ __forceinline__ void cp_async_wait_all() { asm volatile("cp.async.wait_group 0;\n" ::: "memory"); }
__device__ __forceinline__ void prefetch_l2(const void* p) { asm volatile("prefetch.global.L2 [%0];\n" ::"l"(p)); }

__device__ __forceinline__ float tanh_approx(float x) {
    float y;
    asm("tanh.approx.f32 %0, %1;" : "=f"(y) : "f"(x));
    return y;
}
__device__ __forceinline__ uint32_t pack_bf16(float lo, float hi) {
    uint32_t r;
    asm("cvt.rn.bf16x2.f32 %0, %1, %2;" : "=r"(r) : "f"(hi), "f"(lo));
    return r;
}
__device__ __forceinline__ float bf_lo(uint32_t v) { return __uint_as_float(v << 16); }
__device__ __forceinline__ float bf_hi(uint32_t v) { return __uint_as_float(v & 0xffff0000u); }

#define ACC32(d)                                                                                             \
    "+f"(d[0]), "+f"(d[1]), "+f"(d[2]), "+f"(d[3]), "+f"(d[4]), "+f"(d[5]), "+f"(d[6]), "+f"(d[7]),          \
        "+f"(d[8]), "+f"(d[9]), "+f"(d[10]), "+f"(d[11]), "+f"(d[12]), "+f"(d[13]), "+f"(d[14]), "+f"(d[15]), \
        "+f"(d[16]), "+f"(d[17]), "+f"(d[18]), "+f"(d[19]), "+f"(d[20]), "+f"(d[21]), "+f"(d[22]),           \
        "+f"(d[23]), "+f"(d[24]), "+f"(d[25]), "+f"(d[26]), "+f"(d[27]), "+f"(d[28]), "+f"(d[29]),           \
        "+f"(d[30]), "+f"(d[31])
#define ACC32_STR                                                                \
    "{%0, %1, %2, %3, %4, %5, %6, %7, %8, %9, %10, %11, %12, %13, %14, %15, "    \
    " %16, %17, %18, %19, %20, %21, %22, %23, %24, %25, %26, %27, %28, %29, %30, %31}"

__device__ __forceinline__ void wgmma_ss_n64_tA(float (&d)[32], uint64_t adesc, uint64_t bdesc, int scale_d) {
    asm volatile(
        "{\n.reg .pred p;\nsetp.ne.b32 p, %34, 0;\n"
        "wgmma.mma_async.sync.aligned.m64n64k16.f32.bf16.bf16 " ACC32_STR ", %32, %33, p, 1, 1, 1, 0;\n}\n"
        : ACC32(d)
        : "l"(adesc), "l"(bdesc), "r"(scale_d));
}
__device__ __forceinline__ void wgmma_ss_n64(float (&d)[32], uint64_t adesc, uint64_t bdesc, int scale_d) {
    asm volatile(
        "{\n.reg .pred p;\nsetp.ne.b32 p, %34, 0;\n"
        "wgmma.mma_async.sync.aligned.m64n64k16.f32.bf16.bf16 " ACC32_STR ", %32, %33, p, 1, 1, 0, 1;\n}\n"
        : ACC32(d)
        : "l"(adesc), "l"(bdesc), "r"(scale_d));
}
__device__ __forceinline__ void wgmma_n96(float (&d)[48], uint32_t a0, uint32_t a1, uint32_t a2, uint32_t a3,
                                          uint64_t bdesc) {
    asm volatile(
        "{\n"
        "wgmma.mma_async.sync.aligned.m64n96k16.f32.bf16.bf16 "
        "{%0, %1, %2, %3, %4, %5, %6, %7, %8, %9, %10, %11, %12, %13, %14, %15, "
        " %16, %17, %18, %19, %20, %21, %22, %23, %24, %25, %26, %27, %28, %29, %30, %31, "
        " %32, %33, %34, %35, %36, %37, %38, %39, %40, %41, %42, %43, %44, %45, %46, %47}, "
        "{%48, %49, %50, %51}, %52, 1, 1, 1, 1;\n"
        "}\n"
        : ACC32(d), "+f"(d[32]), "+f"(d[33]), "+f"(d[34]), "+f"(d[35]), "+f"(d[36]), "+f"(d[37]), "+f"(d[38]),
          "+f"(d[39]), "+f"(d[40]), "+f"(d[41]), "+f"(d[42]), "+f"(d[43]), "+f"(d[44]), "+f"(d[45]), "+f"(d[46]),
          "+f"(d[47])
        : "r"(a0), "r"(a1), "r"(a2), "r"(a3), "l"(bdesc));
}

#define W2_LBO 128
#define W2_SBO (48 * 128)
#define W1_BOX_BYTES (96 * 128)
#define Y_BOX_BYTES (64 * 64)
#define Y_TILE_BYTES (3 * Y_BOX_BYTES)

__device__ __forceinline__ void ln_row4(const uint4 (&xv)[3], const float* __restrict__ s_dwq, uint4 (&y)[3]) {
    float xf[24], dwf[24];
    float s = 0.f;
#pragma unroll
    for (int i = 0; i < 3; i++) {
        uint32_t w[4] = {xv[i].x, xv[i].y, xv[i].z, xv[i].w};
        float4 da = *reinterpret_cast<const float4*>(s_dwq + 32 * i);
        float4 db = *reinterpret_cast<const float4*>(s_dwq + 32 * i + 4);
        dwf[i * 8 + 0] = da.x; dwf[i * 8 + 1] = da.y; dwf[i * 8 + 2] = da.z; dwf[i * 8 + 3] = da.w;
        dwf[i * 8 + 4] = db.x; dwf[i * 8 + 5] = db.y; dwf[i * 8 + 6] = db.z; dwf[i * 8 + 7] = db.w;
#pragma unroll
        for (int p = 0; p < 4; p++) {
            xf[i * 8 + 2 * p] = bf_lo(w[p]);
            xf[i * 8 + 2 * p + 1] = bf_hi(w[p]);
        }
#pragma unroll
        for (int p = 0; p < 8; p++) s = fmaf(xf[i * 8 + p], dwf[i * 8 + p], s);
    }
    s += __shfl_xor_sync(0xffffffffu, s, 1);
    s += __shfl_xor_sync(0xffffffffu, s, 2);
    float nmean = s * (-1.0f / C_IN);
    float v = 0.f;
#pragma unroll
    for (int i = 0; i < 24; i++) {
        xf[i] = fmaf(xf[i], dwf[i], nmean);
        v = fmaf(xf[i], xf[i], v);
    }
    v += __shfl_xor_sync(0xffffffffu, v, 1);
    v += __shfl_xor_sync(0xffffffffu, v, 2);
    float rstd = rsqrtf(v * (1.0f / C_IN) + 1e-5f) * GELU_KAPPA;
#pragma unroll
    for (int i = 0; i < 3; i++) {
        y[i].x = pack_bf16(xf[i * 8 + 0] * rstd, xf[i * 8 + 1] * rstd);
        y[i].y = pack_bf16(xf[i * 8 + 2] * rstd, xf[i * 8 + 3] * rstd);
        y[i].z = pack_bf16(xf[i * 8 + 4] * rstd, xf[i * 8 + 5] * rstd);
        y[i].w = pack_bf16(xf[i * 8 + 6] * rstd, xf[i * 8 + 7] * rstd);
    }
}

__device__ __forceinline__ void ln_tile_inplace(unsigned char* yp, const float* __restrict__ s_dwq) {
    uint4 xv[3], y[3];
#pragma unroll
    for (int i = 0; i < 3; i++) xv[i] = *reinterpret_cast<const uint4*>(yp + i * Y_BOX_BYTES);
    ln_row4(xv, s_dwq, y);
#pragma unroll
    for (int i = 0; i < 3; i++) *reinterpret_cast<uint4*>(yp + i * Y_BOX_BYTES) = y[i];
#pragma unroll
    for (int i = 0; i < 3; i++) xv[i] = *reinterpret_cast<const uint4*>(yp + 512 + i * Y_BOX_BYTES);
    ln_row4(xv, s_dwq, y);
#pragma unroll
    for (int i = 0; i < 3; i++) *reinterpret_cast<uint4*>(yp + 512 + i * Y_BOX_BYTES) = y[i];
}

__device__ __forceinline__ float gelu2(float u) {
    float t = fmaf(u, u, GELU_C0K);
    float a = t * u;
    float th = tanh_approx(a);
    return fmaf(u, th, u);
}

__device__ __forceinline__ void tma_x_tile(uint32_t dst, const CUtensorMap* tmx, uint32_t bar, int tile) {
    mbar_expect_tx(bar, Y_TILE_BYTES);
#pragma unroll
    for (int i = 0; i < 3; i++) tma_load_2d(dst + i * Y_BOX_BYTES, tmx, bar, i * 32, tile * TILE_M);
}

__global__ void __launch_bounds__(NTHR, 1)
k_stats(const __grid_constant__ CUtensorMap tm_x, const __grid_constant__ CUtensorMap tm_w1,
        const __nv_bfloat16* __restrict__ dw) {
    extern __shared__ __align__(1024) unsigned char smem[];
    unsigned char* s_w1 = smem;
    unsigned char* s_y = smem + 73728;
    float* s_dw = reinterpret_cast<float*>(smem + 73728 + NWG * 2 * Y_TILE_BYTES);
    float* s_red = s_dw + 128;
    uint64_t* s_bar = reinterpret_cast<uint64_t*>(s_red + C_H);

    const int tid = threadIdx.x;
    const int wg = tid >> 7;
    const int warp = (tid >> 5) & 3;
    const int lane = tid & 31;
    const int q = lane & 3;
    const int nwg = gridDim.x * NWG;
    int tile = blockIdx.x * NWG + wg;

    if (tid == 0) {
        for (int i = 0; i < 1 + 2 * NWG; i++) mbar_init(smem_u32(s_bar + i), 1);
        asm volatile("fence.mbarrier_init.release.cluster;\n" ::: "memory");
    }
    if (tid < C_IN) s_dw[tid] = __bfloat162float(dw[tid]);
    for (int i = tid; i < C_H; i += NTHR) s_red[i] = 0.f;
    __syncthreads();
    const uint32_t ybuf0 = smem_u32(s_y + wg * 2 * Y_TILE_BYTES);
    const uint32_t bar_y = smem_u32(s_bar + 1 + 2 * wg);
    if (tid == 0) {
        mbar_expect_tx(smem_u32(s_bar), 6 * W1_BOX_BYTES);
        for (int i = 0; i < 6; i++) tma_load_2d(smem_u32(s_w1) + i * W1_BOX_BYTES, &tm_w1, smem_u32(s_bar), i * 64, 0);
    }
    if ((tid & 127) == 0 && tile < NTILES) tma_x_tile(ybuf0, &tm_x, bar_y, tile);

    asm volatile("griddepcontrol.launch_dependents;\n" ::: "memory");
    float ss[12];
#pragma unroll
    for (int i = 0; i < 12; i++) ss[i] = 0.f;

    const uint64_t w1_desc = make_desc(smem_u32(s_w1), W1_BOX_BYTES, 1024, 1);
    const int rl = warp * 16 + (lane >> 2);
    const int yoff = rl * 64 + ((q ^ ((rl >> 1) & 3)) * 16);
    mbar_wait(smem_u32(s_bar), 0);

    int it = 0;
    for (; tile < NTILES; tile += nwg, it++) {
        const int buf = it & 1;
        if ((tid & 127) == 0 && tile + nwg < NTILES) tma_x_tile(ybuf0 + (buf ^ 1) * Y_TILE_BYTES, &tm_x, bar_y + (buf ^ 1) * 8, tile + nwg);
        mbar_wait(bar_y + buf * 8, (it >> 1) & 1);
        unsigned char* ytile = s_y + (wg * 2 + buf) * Y_TILE_BYTES;
        ln_tile_inplace(ytile + yoff, s_dw + 8 * q);
        proxy_fence();
        wg_bar(1 + wg);
        const uint64_t y_desc = make_desc(smem_u32(ytile), 16, 512, 2);
        float S[2][32];
        wg_fence();
#pragma unroll
        for (int t = 0; t < 6; t++)
            wgmma_ss_n64_tA(S[0], w1_desc + ((t * 2048) >> 4), y_desc + (((t >> 1) * Y_BOX_BYTES + (t & 1) * 32) >> 4), t != 0);
        wg_commit();
#pragma unroll
        for (int m = 0; m < 6; m++) {
            if (m + 1 < 6) {
                wg_fence();
#pragma unroll
                for (int t = 0; t < 6; t++)
                    wgmma_ss_n64_tA(S[(m + 1) & 1], w1_desc + (((m + 1) * W1_BOX_BYTES + t * 2048) >> 4),
                                    y_desc + (((t >> 1) * Y_BOX_BYTES + (t & 1) * 32) >> 4), t != 0);
                wg_commit();
                wg_wait<1>();
            } else {
                wg_wait<0>();
            }
            float(&Sc)[32] = S[m & 1];
            float a0 = ss[2 * m], a1 = ss[2 * m + 1];
#pragma unroll
            for (int j = 0; j < 8; j++) {
                float g0 = gelu2(Sc[4 * j]);
                float g1 = gelu2(Sc[4 * j + 1]);
                float g2 = gelu2(Sc[4 * j + 2]);
                float g3 = gelu2(Sc[4 * j + 3]);
                a0 = fmaf(g0, g0, a0);
                a1 = fmaf(g2, g2, a1);
                a0 = fmaf(g1, g1, a0);
                a1 = fmaf(g3, g3, a1);
            }
            ss[2 * m] = a0;
            ss[2 * m + 1] = a1;
        }
        wg_bar(1 + wg);
    }
#pragma unroll
    for (int i = 0; i < 12; i++) {
        float v = ss[i];
        v += __shfl_xor_sync(0xffffffffu, v, 1);
        v += __shfl_xor_sync(0xffffffffu, v, 2);
        if (q == 0) {
            int m = i >> 1, hh = i & 1;
            atomicAdd(&s_red[m * 64 + warp * 16 + hh * 8 + (lane >> 2)], v);
        }
    }
    __syncthreads();
    const float sc = 0.25f / (GELU_KAPPA * GELU_KAPPA);
    for (int i = tid; i < C_H; i += NTHR) atomicAdd(&g_sum[i], s_red[i] * sc);
}

#define NWG2 2
#define NTHR2 (NWG2 * 128)

__device__ __forceinline__ void wgmma_rs_n64(float (&d)[32], uint32_t a0, uint32_t a1, uint32_t a2, uint32_t a3,
                                             uint64_t bdesc, int scale_d) {
    asm volatile(
        "{\n.reg .pred p;\nsetp.ne.b32 p, %37, 0;\n"
        "wgmma.mma_async.sync.aligned.m64n64k16.f32.bf16.bf16 " ACC32_STR ", {%32, %33, %34, %35}, %36, p, 1, 1, 1;\n}\n"
        : ACC32(d)
        : "r"(a0), "r"(a1), "r"(a2), "r"(a3), "l"(bdesc), "r"(scale_d));
}
__device__ __forceinline__ void ldsm_x4(uint32_t addr, uint32_t& r0, uint32_t& r1, uint32_t& r2, uint32_t& r3) {
    asm volatile("ldmatrix.sync.aligned.m8n8.x4.shared.b16 {%0, %1, %2, %3}, [%4];\n"
                 : "=r"(r0), "=r"(r1), "=r"(r2), "=r"(r3) : "r"(addr) : "memory");
}
__device__ __forceinline__ void stsm_x4(uint32_t addr, uint32_t r0, uint32_t r1, uint32_t r2, uint32_t r3) {
    asm volatile("stmatrix.sync.aligned.m8n8.x4.shared.b16 [%0], {%1, %2, %3, %4};\n" ::"r"(addr), "r"(r0), "r"(r1), "r"(r2),
                 "r"(r3) : "memory");
}
__device__ __forceinline__ void tma_store_2d(const CUtensorMap* tm, uint32_t src, int c0, int c1) {
    asm volatile("cp.async.bulk.tensor.2d.global.shared::cta.bulk_group [%0, {%2, %3}], [%1];\n" ::"l"(
                     reinterpret_cast<uint64_t>(tm)), "r"(src), "r"(c0), "r"(c1) : "memory");
}

__device__ __forceinline__ void ln_frag(uint32_t (&f)[6][4], const float* __restrict__ s_dwq) {
    float xa[24], xb[24], dwf[24];
    float sa = 0.f, sb = 0.f;
#pragma unroll
    for (int t = 0; t < 6; t++) {
#pragma unroll
        for (int h = 0; h < 2; h++) {
            float2 d = *reinterpret_cast<const float2*>(s_dwq + 16 * t + 8 * h);
            int i = t * 4 + h * 2;
            dwf[i] = d.x; dwf[i + 1] = d.y;
            xa[i] = bf_lo(f[t][2 * h]); xa[i + 1] = bf_hi(f[t][2 * h]);
            xb[i] = bf_lo(f[t][2 * h + 1]); xb[i + 1] = bf_hi(f[t][2 * h + 1]);
            sa = fmaf(xa[i], d.x, sa); sa = fmaf(xa[i + 1], d.y, sa);
            sb = fmaf(xb[i], d.x, sb); sb = fmaf(xb[i + 1], d.y, sb);
        }
    }
    sa += __shfl_xor_sync(0xffffffffu, sa, 1);
    sb += __shfl_xor_sync(0xffffffffu, sb, 1);
    sa += __shfl_xor_sync(0xffffffffu, sa, 2);
    sb += __shfl_xor_sync(0xffffffffu, sb, 2);
    float ma = sa * (-1.0f / C_IN), mb = sb * (-1.0f / C_IN);
    float va = 0.f, vb = 0.f;
#pragma unroll
    for (int i = 0; i < 24; i++) {
        xa[i] = fmaf(xa[i], dwf[i], ma);
        xb[i] = fmaf(xb[i], dwf[i], mb);
        va = fmaf(xa[i], xa[i], va);
        vb = fmaf(xb[i], xb[i], vb);
    }
    va += __shfl_xor_sync(0xffffffffu, va, 1);
    vb += __shfl_xor_sync(0xffffffffu, vb, 1);
    va += __shfl_xor_sync(0xffffffffu, va, 2);
    vb += __shfl_xor_sync(0xffffffffu, vb, 2);
    float ra = rsqrtf(va * (1.0f / C_IN) + 1e-5f) * GELU_KAPPA;
    float rb = rsqrtf(vb * (1.0f / C_IN) + 1e-5f) * GELU_KAPPA;
#pragma unroll
    for (int t = 0; t < 6; t++) {
#pragma unroll
        for (int h = 0; h < 2; h++) {
            int i = t * 4 + h * 2;
            f[t][2 * h] = pack_bf16(xa[i] * ra, xa[i + 1] * ra);
            f[t][2 * h + 1] = pack_bf16(xb[i] * rb, xb[i + 1] * rb);
        }
    }
}

__global__ void __launch_bounds__(NTHR2, 1)
k_main(const __grid_constant__ CUtensorMap tm_x, const __grid_constant__ CUtensorMap tm_w1,
       const __grid_constant__ CUtensorMap tm_out, const __grid_constant__ CUtensorMap tm_w2,
       const __nv_bfloat16* __restrict__ dw, const __nv_bfloat16* __restrict__ grn_g,
       const __nv_bfloat16* __restrict__ grn_b) {
    extern __shared__ __align__(1024) unsigned char smem[];
    unsigned char* s_w1 = smem;
    unsigned char* s_w2 = smem + 73728;
    unsigned char* s_x = smem + 2 * 73728;
    float* s_dw = reinterpret_cast<float*>(smem + 2 * 73728 + NWG2 * 2 * Y_TILE_BYTES);
    float* s_c = s_dw + 128;
    float* s_s = s_c + 128;
    float* s_tmp = s_s + C_H;
    uint64_t* s_bar = reinterpret_cast<uint64_t*>(s_tmp + 16);

    const int tid = threadIdx.x;
    const int wg = tid >> 7;
    const int warp = (tid >> 5) & 3;
    const int lane = tid & 31;
    const int q = lane & 3;
    const int nwg = gridDim.x * NWG2;
    int tile = blockIdx.x * NWG2 + wg;

    const uint32_t xbuf0 = smem_u32(s_x + wg * 2 * Y_TILE_BYTES);
    const uint32_t bar_x = smem_u32(s_bar + 1 + 2 * wg);
    if (tid == 0) {
        for (int i = 0; i < 1 + 2 * NWG2; i++) mbar_init(smem_u32(s_bar + i), 1);
        asm volatile("fence.mbarrier_init.release.cluster;\n" ::: "memory");
    }
    if (tid < C_IN) { s_dw[tid] = __bfloat162float(dw[tid]); s_c[tid] = 0.f; }
    __syncthreads();
    if (tid == 0) {
        mbar_expect_tx(smem_u32(s_bar), 6 * W1_BOX_BYTES + 73728);
        for (int i = 0; i < 6; i++) tma_load_2d(smem_u32(s_w1) + i * W1_BOX_BYTES, &tm_w1, smem_u32(s_bar), i * 64, 0);
        for (int g = 0; g < 3; g++)
            for (int i = 0; i < 3; i++)
                tma_load_2d(smem_u32(s_w2) + g * 24576 + i * 8192, &tm_w2, smem_u32(s_bar), g * 32, i * 128);
    }
    if ((tid & 127) == 0 && tile < NTILES) tma_x_tile(xbuf0, &tm_x, bar_x, tile);
    float gg[2];
    gg[0] = __bfloat162float(grn_g[tid]);
    gg[1] = (tid + NTHR2 < C_H) ? __bfloat162float(grn_g[tid + NTHR2]) : 0.f;
    asm volatile("griddepcontrol.wait;\n" ::: "memory");
    float lsum = 0.f;
    for (int k = tid; k < C_H; k += NTHR2) {
        float gx = sqrtf(__ldcg(&g_sum[k]) + 1e-6f);
        s_s[k] = gx;
        lsum += gx;
    }
#pragma unroll
    for (int o = 16; o > 0; o >>= 1) lsum += __shfl_xor_sync(0xffffffffu, lsum, o);
    if (lane == 0) s_tmp[tid >> 5] = lsum;
    __syncthreads();
    __shared__ unsigned int s_last;
    if (tid == 0) s_last = (atomicAdd(&g_done, 1u) == gridDim.x - 1);
    float tot = 0.f;
#pragma unroll
    for (int i = 0; i < NTHR2 / 32; i++) tot += s_tmp[i];
    float inv = 1.0f / (tot * (1.0f / C_H) + 1e-6f);
    {
        int j = 0;
        for (int k = tid; k < C_H; k += NTHR2, j++) s_s[k] = (0.5f / GELU_KAPPA) * (1.0f + gg[j] * (s_s[k] * inv));
    }
    __syncthreads();
    if (s_last) {
        for (int k = tid; k < C_H; k += NTHR2) g_sum[k] = 0.f;
        if (tid == 0) g_done = 0;
    }
    mbar_wait(smem_u32(s_bar), 0);
    if (tid < 252) {
        const int nc = tid % 12, k0 = tid / 12;
        float acc[8];
#pragma unroll
        for (int e = 0; e < 8; e++) acc[e] = 0.f;
        for (int k = k0; k < C_H; k += 21) {
            uint4* ptr = reinterpret_cast<uint4*>(s_w2 + (nc >> 2) * 24576 + k * 64 + (((nc & 3) ^ ((k >> 1) & 3)) << 4));
            uint4 v = *ptr;
            float sk = s_s[k], b = __bfloat162float(grn_b[k]);
            float f0 = bf_lo(v.x), f1 = bf_hi(v.x), f2 = bf_lo(v.y), f3 = bf_hi(v.y);
            float f4 = bf_lo(v.z), f5 = bf_hi(v.z), f6 = bf_lo(v.w), f7 = bf_hi(v.w);
            acc[0] = fmaf(b, f0, acc[0]); acc[1] = fmaf(b, f1, acc[1]); acc[2] = fmaf(b, f2, acc[2]); acc[3] = fmaf(b, f3, acc[3]);
            acc[4] = fmaf(b, f4, acc[4]); acc[5] = fmaf(b, f5, acc[5]); acc[6] = fmaf(b, f6, acc[6]); acc[7] = fmaf(b, f7, acc[7]);
            uint4 o;
            o.x = pack_bf16(sk * f0, sk * f1); o.y = pack_bf16(sk * f2, sk * f3);
            o.z = pack_bf16(sk * f4, sk * f5); o.w = pack_bf16(sk * f6, sk * f7);
            *ptr = o;
        }
#pragma unroll
        for (int e = 0; e < 8; e++) atomicAdd(&s_c[nc * 8 + e], acc[e]);
    }
    proxy_fence();
    __syncthreads();

    const uint64_t w1_desc = make_desc(smem_u32(s_w1), W1_BOX_BYTES, 1024, 1);
    const uint64_t w2_desc = make_desc(smem_u32(s_w2), 24576, 512, 2);
    const int lrow = warp * 16 + ((lane >> 3) & 1) * 8 + (lane & 7);
    const int lhalf = lane >> 4;
    const int lsw = (lrow >> 1) & 3;
    const uint32_t loff0 = lrow * 64 + (((0 + lhalf) ^ lsw) << 4);
    const uint32_t loff1 = lrow * 64 + (((2 + lhalf) ^ lsw) << 4);

    int it = 0;
    for (; tile < NTILES; tile += nwg, it++) {
        const int buf = it & 1;
        const uint32_t xb = xbuf0 + buf * Y_TILE_BYTES;
        if ((tid & 127) == 0 && tile + nwg < NTILES) {
            asm volatile("cp.async.bulk.wait_group.read 0;\n" ::: "memory");
            tma_x_tile(xbuf0 + (buf ^ 1) * Y_TILE_BYTES, &tm_x, bar_x + (buf ^ 1) * 8, tile + nwg);
        }
        mbar_wait(bar_x + buf * 8, (it >> 1) & 1);
        uint32_t f[6][4];
#pragma unroll
        for (int t = 0; t < 6; t++)
            ldsm_x4(xb + (t >> 1) * Y_BOX_BYTES + ((t & 1) ? loff1 : loff0), f[t][0], f[t][1], f[t][2], f[t][3]);
        ln_frag(f, s_dw + 2 * q);

        float O[48];
#pragma unroll
        for (int j = 0; j < 12; j++) {
            float2 cc = *reinterpret_cast<const float2*>(&s_c[8 * j + 2 * q]);
            O[4 * j] = cc.x; O[4 * j + 1] = cc.y; O[4 * j + 2] = cc.x; O[4 * j + 3] = cc.y;
        }
        float S[2][32];
        uint32_t hf[2][16];
        wg_fence();
#pragma unroll
        for (int t = 0; t < 6; t++) wgmma_rs_n64(S[0], f[t][0], f[t][1], f[t][2], f[t][3], w1_desc + ((t * 2048) >> 4), t != 0);
        wg_commit();
#pragma unroll
        for (int c = 0; c < 6; c++) {
            if (c + 1 < 6) {
                wg_fence();
#pragma unroll
                for (int t = 0; t < 6; t++)
                    wgmma_rs_n64(S[(c + 1) & 1], f[t][0], f[t][1], f[t][2], f[t][3],
                                 w1_desc + (((c + 1) * W1_BOX_BYTES + t * 2048) >> 4), t != 0);
                wg_commit();
                if (c == 0) wg_wait<1>(); else wg_wait<2>();
            } else {
                wg_wait<1>();
            }
            float(&Sc)[32] = S[c & 1];
            uint32_t(&h)[16] = hf[c & 1];
#pragma unroll
            for (int j = 0; j < 8; j++) {
                float g0 = gelu2(Sc[4 * j]);
                float g1 = gelu2(Sc[4 * j + 1]);
                float g2 = gelu2(Sc[4 * j + 2]);
                float g3 = gelu2(Sc[4 * j + 3]);
                h[2 * j] = pack_bf16(g0, g1);
                h[2 * j + 1] = pack_bf16(g2, g3);
            }
            wg_fence();
#pragma unroll
            for (int t = 0; t < 4; t++)
                wgmma_n96(O, h[4 * t], h[4 * t + 1], h[4 * t + 2], h[4 * t + 3],
                          w2_desc + (((c * 64 + 16 * t) * 64) >> 4));
            wg_commit();
        }
        uint32_t xr[6][4];
#pragma unroll
        for (int t = 0; t < 6; t++)
            ldsm_x4(xb + (t >> 1) * Y_BOX_BYTES + ((t & 1) ? loff1 : loff0), xr[t][0], xr[t][1], xr[t][2], xr[t][3]);
        wg_wait<0>();
#pragma unroll
        for (int t = 0; t < 6; t++) {
            uint32_t o0 = pack_bf16(bf_lo(xr[t][0]) + O[8 * t + 0], bf_hi(xr[t][0]) + O[8 * t + 1]);
            uint32_t o1 = pack_bf16(bf_lo(xr[t][1]) + O[8 * t + 2], bf_hi(xr[t][1]) + O[8 * t + 3]);
            uint32_t o2 = pack_bf16(bf_lo(xr[t][2]) + O[8 * t + 4], bf_hi(xr[t][2]) + O[8 * t + 5]);
            uint32_t o3 = pack_bf16(bf_lo(xr[t][3]) + O[8 * t + 6], bf_hi(xr[t][3]) + O[8 * t + 7]);
            stsm_x4(xb + (t >> 1) * Y_BOX_BYTES + ((t & 1) ? loff1 : loff0), o0, o1, o2, o3);
        }
        proxy_fence();
        wg_bar(1 + wg);
        if ((tid & 127) == 0) {
#pragma unroll
            for (int i = 0; i < 3; i++) tma_store_2d(&tm_out, xb + i * Y_BOX_BYTES, i * 32, tile * TILE_M);
            asm volatile("cp.async.bulk.commit_group;\n" ::: "memory");
        }
    }
    if ((tid & 127) == 0) asm volatile("cp.async.bulk.wait_group 0;\n" ::: "memory");
}

#define SMEM1 (73728 + NWG * 2 * Y_TILE_BYTES + 512 + 1536 + 128)
#define SMEM2 (2 * 73728 + NWG2 * 2 * Y_TILE_BYTES + 512 + 512 + 1536 + 64 + 64)

typedef CUresult (*PFN_encodeTiled)(CUtensorMap*, CUtensorMapDataType, cuuint32_t, void*, const cuuint64_t*, const cuuint64_t*,
                                    const cuuint32_t*, const cuuint32_t*, CUtensorMapInterleave, CUtensorMapSwizzle,
                                    CUtensorMapL2promotion, CUtensorMapFloatOOBfill);

extern "C" void kernel_launch(void* const* d_in, const int* in_sizes, int n_in, void* d_out, int out_size) {
    const __nv_bfloat16* x = (const __nv_bfloat16*)d_in[0];
    const __nv_bfloat16* dw = (const __nv_bfloat16*)d_in[1];
    const __nv_bfloat16* w1 = (const __nv_bfloat16*)d_in[2];
    const __nv_bfloat16* w2 = (const __nv_bfloat16*)d_in[3];
    const __nv_bfloat16* grn_g = (const __nv_bfloat16*)d_in[4];
    const __nv_bfloat16* grn_b = (const __nv_bfloat16*)d_in[5];

    static int n_sm = 0;
    static CUtensorMap tm_x, tm_w1, tm_out, tm_w2;
    static const void* last_x = nullptr;
    static const void* last_w1 = nullptr;
    static const void* last_out = nullptr;
    static const void* last_w2 = nullptr;
    static PFN_encodeTiled encode = nullptr;
    if (n_sm == 0) {
        int dev = 0;
        cudaGetDevice(&dev);
        cudaDeviceGetAttribute(&n_sm, cudaDevAttrMultiProcessorCount, dev);
        if (n_sm > MAX_CTAS) n_sm = MAX_CTAS;
        cudaFuncSetAttribute(k_stats, cudaFuncAttributeMaxDynamicSharedMemorySize, SMEM1);
        cudaFuncSetAttribute(k_main, cudaFuncAttributeMaxDynamicSharedMemorySize, SMEM2);
        cudaDriverEntryPointQueryResult qres;
        void* fn = nullptr;
        cudaGetDriverEntryPoint("cuTensorMapEncodeTiled", &fn, cudaEnableDefault, &qres);
        encode = (PFN_encodeTiled)fn;
    }
    if (last_x != x || last_w1 != w1 || last_out != d_out || last_w2 != w2) {
        cuuint64_t dims[2] = {96, (cuuint64_t)NROWS};
        cuuint64_t strides[1] = {192};
        cuuint32_t box[2] = {32, 64};
        cuuint32_t es[2] = {1, 1};
        encode(&tm_x, CU_TENSOR_MAP_DATA_TYPE_BFLOAT16, 2, (void*)x, dims, strides, box, es, CU_TENSOR_MAP_INTERLEAVE_NONE,
               CU_TENSOR_MAP_SWIZZLE_64B, CU_TENSOR_MAP_L2_PROMOTION_L2_128B, CU_TENSOR_MAP_FLOAT_OOB_FILL_NONE);
        encode(&tm_out, CU_TENSOR_MAP_DATA_TYPE_BFLOAT16, 2, d_out, dims, strides, box, es, CU_TENSOR_MAP_INTERLEAVE_NONE,
               CU_TENSOR_MAP_SWIZZLE_64B, CU_TENSOR_MAP_L2_PROMOTION_L2_128B, CU_TENSOR_MAP_FLOAT_OOB_FILL_NONE);
        cuuint64_t dimsw[2] = {384, 96};
        cuuint64_t stridesw[1] = {768};
        cuuint32_t boxw[2] = {64, 96};
        encode(&tm_w1, CU_TENSOR_MAP_DATA_TYPE_BFLOAT16, 2, (void*)w1, dimsw, stridesw, boxw, es, CU_TENSOR_MAP_INTERLEAVE_NONE,
               CU_TENSOR_MAP_SWIZZLE_128B, CU_TENSOR_MAP_L2_PROMOTION_L2_128B, CU_TENSOR_MAP_FLOAT_OOB_FILL_NONE);
        cuuint64_t dims2[2] = {96, 384};
        cuuint32_t box2[2] = {32, 128};
        encode(&tm_w2, CU_TENSOR_MAP_DATA_TYPE_BFLOAT16, 2, (void*)w2, dims2, strides, box2, es, CU_TENSOR_MAP_INTERLEAVE_NONE,
               CU_TENSOR_MAP_SWIZZLE_64B, CU_TENSOR_MAP_L2_PROMOTION_L2_128B, CU_TENSOR_MAP_FLOAT_OOB_FILL_NONE);
        last_x = x;
        last_w1 = w1;
        last_out = d_out;
        last_w2 = w2;
    }
    k_stats<<<n_sm, NTHR, SMEM1>>>(tm_x, tm_w1, dw);
    cudaLaunchConfig_t cfg = {};
    cfg.gridDim = dim3(n_sm);
    cfg.blockDim = dim3(NTHR2);
    cfg.dynamicSmemBytes = SMEM2;
    cfg.stream = cudaStreamPerThread;
    cudaLaunchAttribute attr[1];
    attr[0].id = cudaLaunchAttributeProgrammaticStreamSerialization;
    attr[0].val.programmaticStreamSerializationAllowed = 1;
    cfg.attrs = attr;
    cfg.numAttrs = 1;
    cudaLaunchKernelEx(&cfg, k_main, tm_x, tm_w1, tm_out, tm_w2, dw, grn_g, grn_b);
}
```

```cpp
#include <cuda_runtime.h>
#include <cuda_bf16.h>
#include <stdint.h>
#include <cuda.h>

#define C_IN 96
#define C_H 384
#define NROWS (512 * 512)
#define TILE_M 64
#define NTILES (NROWS / TILE_M)
#define MAX_CTAS 256
#define NWG 4
#define NTHR (NWG * 128)

__device__ float g_sum[C_H];
__device__ unsigned int g_done;

#define TSTAMP(i)

#define GELU_KAPPA 0.3292034911525734f
#define GELU_C0K 2.423681954311584f

__device__ __forceinline__ uint32_t smem_u32(const void* p) { return (uint32_t)__cvta_generic_to_shared(p); }
__device__ __forceinline__ uint64_t make_desc(uint32_t addr, uint32_t lbo, uint32_t sbo, uint32_t swz = 0) {
    uint64_t d = 0;
    d |= (uint64_t)((addr & 0x3FFFF) >> 4);
    d |= (uint64_t)((lbo >> 4) & 0x3FFF) << 16;
    d |= (uint64_t)((sbo >> 4) & 0x3FFF) << 32;
    d |= (uint64_t)swz << 62;
    return d;
}
__device__ __forceinline__ void mbar_init(uint32_t bar, uint32_t count) {
    asm volatile("mbarrier.init.shared::cta.b64 [%0], %1;\n" ::"r"(bar), "r"(count) : "memory");
}
__device__ __forceinline__ void mbar_expect_tx(uint32_t bar, uint32_t bytes) {
    asm volatile("mbarrier.arrive.expect_tx.shared::cta.b64 _, [%0], %1;\n" ::"r"(bar), "r"(bytes) : "memory");
}
__device__ __forceinline__ void mbar_wait(uint32_t bar, uint32_t parity) {
    asm volatile(
        "{\n.reg .pred p;\n"
        "WAIT_LOOP:\n"
        "mbarrier.try_wait.parity.shared::cta.b64 p, [%0], %1;\n"
        "@p bra WAIT_DONE;\n"
        "bra WAIT_LOOP;\n"
        "WAIT_DONE:\n}\n" ::"r"(bar), "r"(parity) : "memory");
}
__device__ __forceinline__ void tma_load_2d(uint32_t dst, const CUtensorMap* tm, uint32_t bar, int c0, int c1) {
    asm volatile(
        "cp.async.bulk.tensor.2d.shared::cluster.global.mbarrier::complete_tx::bytes [%0], [%1, {%3, %4}], [%2];\n" ::"r"(dst),
        "l"(reinterpret_cast<uint64_t>(tm)), "r"(bar), "r"(c0), "r"(c1)
        : "memory");
}
__device__ __forceinline__ void wg_fence() { asm volatile("wgmma.fence.sync.aligned;\n" ::: "memory"); }
__device__ __forceinline__ void wg_commit() { asm volatile("wgmma.commit_group.sync.aligned;\n" ::: "memory"); }
template <int N>
__device__ __forceinline__ void wg_wait() { asm volatile("wgmma.wait_group.sync.aligned %0;\n" ::"n"(N) : "memory"); }
__device__ __forceinline__ void wg_bar(int id) { asm volatile("bar.sync %0, 128;" ::"r"(id) : "memory"); }
__device__ __forceinline__ void proxy_fence() {
 asm volatile("fence.proxy.async.shared::cta;\n" ::: "memory"); }
__device__ __forceinline__ void cp_async16(uint32_t dst, const void* src) {
    asm volatile("cp.async.cg.shared.global [%0], [%1], 16;\n" ::"r"(dst), "l"(src) : "memory");
}
__device__ __forceinline__ void cp_async_commit() { asm volatile("cp.async.commit_group;\n" ::: "memory"); }
__device__ __forceinline__ void cp_async_wait_all() { asm volatile("cp.async.wait_group 0;\n" ::: "memory"); }
__device__ __forceinline__ void prefetch_l2(const void* p) { asm volatile("prefetch.global.L2 [%0];\n" ::"l"(p)); }

__device__ __forceinline__ float tanh_approx(float x) {
    float y;
    asm("tanh.approx.f32 %0, %1;" : "=f"(y) : "f"(x));
    return y;
}
__device__ __forceinline__ uint32_t pack_bf16(float lo, float hi) {
    uint32_t r;
    asm("cvt.rn.bf16x2.f32 %0, %1, %2;" : "=r"(r) : "f"(hi), "f"(lo));
    return r;
}
__device__ __forceinline__ float bf_lo(uint32_t v) { return __uint_as_float(v << 16); }
__device__ __forceinline__ float bf_hi(uint32_t v) { return __uint_as_float(v & 0xffff0000u); }

#define ACC32(d)                                                                                             \
    "+f"(d[0]), "+f"(d[1]), "+f"(d[2]), "+f"(d[3]), "+f"(d[4]), "+f"(d[5]), "+f"(d[6]), "+f"(d[7]),          \
        "+f"(d[8]), "+f"(d[9]), "+f"(d[10]), "+f"(d[11]), "+f"(d[12]), "+f"(d[13]), "+f"(d[14]), "+f"(d[15]), \
        "+f"(d[16]), "+f"(d[17]), "+f"(d[18]), "+f"(d[19]), "+f"(d[20]), "+f"(d[21]), "+f"(d[22]),           \
        "+f"(d[23]), "+f"(d[24]), "+f"(d[25]), "+f"(d[26]), "+f"(d[27]), "+f"(d[28]), "+f"(d[29]),           \
        "+f"(d[30]), "+f"(d[31])
#define ACC32_STR                                                                \
    "{%0, %1, %2, %3, %4, %5, %6, %7, %8, %9, %10, %11, %12, %13, %14, %15, "    \
    " %16, %17, %18, %19, %20, %21, %22, %23, %24, %25, %26, %27, %28, %29, %30, %31}"

__device__ __forceinline__ void wgmma_ss_n64_tA(float (&d)[32], uint64_t adesc, uint64_t bdesc, int scale_d) {
    asm volatile(
        "{\n.reg .pred p;\nsetp.ne.b32 p, %34, 0;\n"
        "wgmma.mma_async.sync.aligned.m64n64k16.f32.bf16.bf16 " ACC32_STR ", %32, %33, p, 1, 1, 1, 0;\n}\n"
        : ACC32(d)
        : "l"(adesc), "l"(bdesc), "r"(scale_d));
}
__device__ __forceinline__ void wgmma_ss_n64(float (&d)[32], uint64_t adesc, uint64_t bdesc, int scale_d) {
    asm volatile(
        "{\n.reg .pred p;\nsetp.ne.b32 p, %34, 0;\n"
        "wgmma.mma_async.sync.aligned.m64n64k16.f32.bf16.bf16 " ACC32_STR ", %32, %33, p, 1, 1, 0, 1;\n}\n"
        : ACC32(d)
        : "l"(adesc), "l"(bdesc), "r"(scale_d));
}
__device__ __forceinline__ void wgmma_n96(float (&d)[48], uint32_t a0, uint32_t a1, uint32_t a2, uint32_t a3,
                                          uint64_t bdesc) {
    asm volatile(
        "{\n"
        "wgmma.mma_async.sync.aligned.m64n96k16.f32.bf16.bf16 "
        "{%0, %1, %2, %3, %4, %5, %6, %7, %8, %9, %10, %11, %12, %13, %14, %15, "
        " %16, %17, %18, %19, %20, %21, %22, %23, %24, %25, %26, %27, %28, %29, %30, %31, "
        " %32, %33, %34, %35, %36, %37, %38, %39, %40, %41, %42, %43, %44, %45, %46, %47}, "
        "{%48, %49, %50, %51}, %52, 1, 1, 1, 1;\n"
        "}\n"
        : ACC32(d), "+f"(d[32]), "+f"(d[33]), "+f"(d[34]), "+f"(d[35]), "+f"(d[36]), "+f"(d[37]), "+f"(d[38]),
          "+f"(d[39]), "+f"(d[40]), "+f"(d[41]), "+f"(d[42]), "+f"(d[43]), "+f"(d[44]), "+f"(d[45]), "+f"(d[46]),
          "+f"(d[47])
        : "r"(a0), "r"(a1), "r"(a2), "r"(a3), "l"(bdesc));
}

#define W2_LBO 128
#define W2_SBO (48 * 128)
#define W1_BOX_BYTES (96 * 128)
#define Y_BOX_BYTES (64 * 64)
#define Y_TILE_BYTES (3 * Y_BOX_BYTES)

__device__ __forceinline__ void ln_row4(const uint4 (&xv)[3], const float* __restrict__ s_dwq, uint4 (&y)[3]) {
    float xf[24], dwf[24];
    float s = 0.f;
#pragma unroll
    for (int i = 0; i < 3; i++) {
        uint32_t w[4] = {xv[i].x, xv[i].y, xv[i].z, xv[i].w};
        float4 da = *reinterpret_cast<const float4*>(s_dwq + 32 * i);
        float4 db = *reinterpret_cast<const float4*>(s_dwq + 32 * i + 4);
        dwf[i * 8 + 0] = da.x; dwf[i * 8 + 1] = da.y; dwf[i * 8 + 2] = da.z; dwf[i * 8 + 3] = da.w;
        dwf[i * 8 + 4] = db.x; dwf[i * 8 + 5] = db.y; dwf[i * 8 + 6] = db.z; dwf[i * 8 + 7] = db.w;
#pragma unroll
        for (int p = 0; p < 4; p++) {
            xf[i * 8 + 2 * p] = bf_lo(w[p]);
            xf[i * 8 + 2 * p + 1] = bf_hi(w[p]);
        }
#pragma unroll
        for (int p = 0; p < 8; p++) s = fmaf(xf[i * 8 + p], dwf[i * 8 + p], s);
    }
    s += __shfl_xor_sync(0xffffffffu, s, 1);
    s += __shfl_xor_sync(0xffffffffu, s, 2);
    float nmean = s * (-1.0f / C_IN);
    float v = 0.f;
#pragma unroll
    for (int i = 0; i < 24; i++) {
        xf[i] = fmaf(xf[i], dwf[i], nmean);
        v = fmaf(xf[i], xf[i], v);
    }
    v += __shfl_xor_sync(0xffffffffu, v, 1);
    v += __shfl_xor_sync(0xffffffffu, v, 2);
    float rstd = rsqrtf(v * (1.0f / C_IN) + 1e-5f) * GELU_KAPPA;
#pragma unroll
    for (int i = 0; i < 3; i++) {
        y[i].x = pack_bf16(xf[i * 8 + 0] * rstd, xf[i * 8 + 1] * rstd);
        y[i].y = pack_bf16(xf[i * 8 + 2] * rstd, xf[i * 8 + 3] * rstd);
        y[i].z = pack_bf16(xf[i * 8 + 4] * rstd, xf[i * 8 + 5] * rstd);
        y[i].w = pack_bf16(xf[i * 8 + 6] * rstd, xf[i * 8 + 7] * rstd);
    }
}

__device__ __forceinline__ void ln_tile_inplace(unsigned char* yp, const float* __restrict__ s_dwq) {
    uint4 xv[3], y[3];
#pragma unroll
    for (int i = 0; i < 3; i++) xv[i] = *reinterpret_cast<const uint4*>(yp + i * Y_BOX_BYTES);
    ln_row4(xv, s_dwq, y);
#pragma unroll
    for (int i = 0; i < 3; i++) *reinterpret_cast<uint4*>(yp + i * Y_BOX_BYTES) = y[i];
#pragma unroll
    for (int i = 0; i < 3; i++) xv[i] = *reinterpret_cast<const uint4*>(yp + 512 + i * Y_BOX_BYTES);
    ln_row4(xv, s_dwq, y);
#pragma unroll
    for (int i = 0; i < 3; i++) *reinterpret_cast<uint4*>(yp + 512 + i * Y_BOX_BYTES) = y[i];
}

__device__ __forceinline__ float gelu2(float u) {
    float t = fmaf(u, u, GELU_C0K);
    float a = t * u;
    float th = tanh_approx(a);
    return fmaf(u, th, u);
}

__device__ __forceinline__ void tma_x_tile(uint32_t dst, const CUtensorMap* tmx, uint32_t bar, int tile) {
    mbar_expect_tx(bar, Y_TILE_BYTES);
#pragma unroll
    for (int i = 0; i < 3; i++) tma_load_2d(dst + i * Y_BOX_BYTES, tmx, bar, i * 32, tile * TILE_M);
}

__global__ void __launch_bounds__(NTHR, 1)
k_stats(const __grid_constant__ CUtensorMap tm_x, const __grid_constant__ CUtensorMap tm_w1,
        const __nv_bfloat16* __restrict__ dw) {
    extern __shared__ __align__(1024) unsigned char smem[];
    unsigned char* s_w1 = smem;
    unsigned char* s_y = smem + 73728;
    float* s_dw = reinterpret_cast<float*>(smem + 73728 + NWG * 2 * Y_TILE_BYTES);
    float* s_red = s_dw + 128;
    uint64_t* s_bar = reinterpret_cast<uint64_t*>(s_red + C_H);

    const int tid = threadIdx.x;
    const int wg = tid >> 7;
    const int warp = (tid >> 5) & 3;
    const int lane = tid & 31;
    const int q = lane & 3;
    const int nwg = gridDim.x * NWG;
    int tile = blockIdx.x * NWG + wg;

    if (tid == 0) {
        for (int i = 0; i < 1 + 2 * NWG; i++) mbar_init(smem_u32(s_bar + i), 1);
        asm volatile("fence.mbarrier_init.release.cluster;\n" ::: "memory");
    }
    if (tid < C_IN) s_dw[tid] = __bfloat162float(dw[tid]);
    for (int i = tid; i < C_H; i += NTHR) s_red[i] = 0.f;
    __syncthreads();
    const uint32_t ybuf0 = smem_u32(s_y + wg * 2 * Y_TILE_BYTES);
    const uint32_t bar_y = smem_u32(s_bar + 1 + 2 * wg);
    if (tid == 0) {
        mbar_expect_tx(smem_u32(s_bar), 6 * W1_BOX_BYTES);
        for (int i = 0; i < 6; i++) tma_load_2d(smem_u32(s_w1) + i * W1_BOX_BYTES, &tm_w1, smem_u32(s_bar), i * 64, 0);
    }
    if ((tid & 127) == 0 && tile < NTILES) tma_x_tile(ybuf0, &tm_x, bar_y, tile);

    asm volatile("griddepcontrol.launch_dependents;\n" ::: "memory");
    float ss[12];
#pragma unroll
    for (int i = 0; i < 12; i++) ss[i] = 0.f;

    const uint64_t w1_desc = make_desc(smem_u32(s_w1), W1_BOX_BYTES, 1024, 1);
    const int rl = warp * 16 + (lane >> 2);
    const int yoff = rl * 64 + ((q ^ ((rl >> 1) & 3)) * 16);
    mbar_wait(smem_u32(s_bar), 0);

    int it = 0;
    for (; tile < NTILES; tile += nwg, it++) {
        const int buf = it & 1;
        if ((tid & 127) == 0 && tile + nwg < NTILES) tma_x_tile(ybuf0 + (buf ^ 1) * Y_TILE_BYTES, &tm_x, bar_y + (buf ^ 1) * 8, tile + nwg);
        mbar_wait(bar_y + buf * 8, (it >> 1) & 1);
        unsigned char* ytile = s_y + (wg * 2 + buf) * Y_TILE_BYTES;
        ln_tile_inplace(ytile + yoff, s_dw + 8 * q);
        proxy_fence();
        wg_bar(1 + wg);
        const uint64_t y_desc = make_desc(smem_u32(ytile), 16, 512, 2);
        float S[2][32];
        wg_fence();
#pragma unroll
        for (int t = 0; t < 6; t++)
            wgmma_ss_n64_tA(S[0], w1_desc + ((t * 2048) >> 4), y_desc + (((t >> 1) * Y_BOX_BYTES + (t & 1) * 32) >> 4), t != 0);
        wg_commit();
#pragma unroll
        for (int m = 0; m < 6; m++) {
            if (m + 1 < 6) {
                wg_fence();
#pragma unroll
                for (int t = 0; t < 6; t++)
                    wgmma_ss_n64_tA(S[(m + 1) & 1], w1_desc + (((m + 1) * W1_BOX_BYTES + t * 2048) >> 4),
                                    y_desc + (((t >> 1) * Y_BOX_BYTES + (t & 1) * 32) >> 4), t != 0);
                wg_commit();
                wg_wait<1>();
            } else {
                wg_wait<0>();
            }
            float(&Sc)[32] = S[m & 1];
            float a0 = ss[2 * m], a1 = ss[2 * m + 1];
#pragma unroll
            for (int j = 0; j < 8; j++) {
                float g0 = gelu2(Sc[4 * j]);
                float g1 = gelu2(Sc[4 * j + 1]);
                float g2 = gelu2(Sc[4 * j + 2]);
                float g3 = gelu2(Sc[4 * j + 3]);
                a0 = fmaf(g0, g0, a0);
                a1 = fmaf(g2, g2, a1);
                a0 = fmaf(g1, g1, a0);
                a1 = fmaf(g3, g3, a1);
            }
            ss[2 * m] = a0;
            ss[2 * m + 1] = a1;
        }
        wg_bar(1 + wg);
    }
#pragma unroll
    for (int i = 0; i < 12; i++) {
        float v = ss[i];
        v += __shfl_xor_sync(0xffffffffu, v, 1);
        v += __shfl_xor_sync(0xffffffffu, v, 2);
        if (q == 0) {
            int m = i >> 1, hh = i & 1;
            atomicAdd(&s_red[m * 64 + warp * 16 + hh * 8 + (lane >> 2)], v);
        }
    }
    __syncthreads();
    const float sc = 0.25f / (GELU_KAPPA * GELU_KAPPA);
    for (int i = tid; i < C_H; i += NTHR) atomicAdd(&g_sum[i], s_red[i] * sc);
}

#define NWG2 2
#define NTHR2 (NWG2 * 128)

__device__ __forceinline__ void wgmma_rs_n64(float (&d)[32], uint32_t a0, uint32_t a1, uint32_t a2, uint32_t a3,
                                             uint64_t bdesc, int scale_d) {
    asm volatile(
        "{\n.reg .pred p;\nsetp.ne.b32 p, %37, 0;\n"
        "wgmma.mma_async.sync.aligned.m64n64k16.f32.bf16.bf16 " ACC32_STR ", {%32, %33, %34, %35}, %36, p, 1, 1, 1;\n}\n"
        : ACC32(d)
        : "r"(a0), "r"(a1), "r"(a2), "r"(a3), "l"(bdesc), "r"(scale_d));
}
__device__ __forceinline__ void ldsm_x4(uint32_t addr, uint32_t& r0, uint32_t& r1, uint32_t& r2, uint32_t& r3) {
    asm volatile("ldmatrix.sync.aligned.m8n8.x4.shared.b16 {%0, %1, %2, %3}, [%4];\n"
                 : "=r"(r0), "=r"(r1), "=r"(r2), "=r"(r3) : "r"(addr) : "memory");
}
__device__ __forceinline__ void stsm_x4(uint32_t addr, uint32_t r0, uint32_t r1, uint32_t r2, uint32_t r3) {
    asm volatile("stmatrix.sync.aligned.m8n8.x4.shared.b16 [%0], {%1, %2, %3, %4};\n" ::"r"(addr), "r"(r0), "r"(r1), "r"(r2),
                 "r"(r3) : "memory");
}
__device__ __forceinline__ void tma_store_2d(const CUtensorMap* tm, uint32_t src, int c0, int c1) {
    asm volatile("cp.async.bulk.tensor.2d.global.shared::cta.bulk_group [%0, {%2, %3}], [%1];\n" ::"l"(
                     reinterpret_cast<uint64_t>(tm)), "r"(src), "r"(c0), "r"(c1) : "memory");
}

__device__ __forceinline__ void ln_frag(uint32_t (&f)[6][4], const float* __restrict__ s_dwq) {
    float xa[24], xb[24], dwf[24];
    float sa = 0.f, sb = 0.f;
#pragma unroll
    for (int t = 0; t < 6; t++) {
#pragma unroll
        for (int h = 0; h < 2; h++) {
            float2 d = *reinterpret_cast<const float2*>(s_dwq + 16 * t + 8 * h);
            int i = t * 4 + h * 2;
            dwf[i] = d.x; dwf[i + 1] = d.y;
            xa[i] = bf_lo(f[t][2 * h]); xa[i + 1] = bf_hi(f[t][2 * h]);
            xb[i] = bf_lo(f[t][2 * h + 1]); xb[i + 1] = bf_hi(f[t][2 * h + 1]);
            sa = fmaf(xa[i], d.x, sa); sa = fmaf(xa[i + 1], d.y, sa);
            sb = fmaf(xb[i], d.x, sb); sb = fmaf(xb[i + 1], d.y, sb);
        }
    }
    sa += __shfl_xor_sync(0xffffffffu, sa, 1);
    sb += __shfl_xor_sync(0xffffffffu, sb, 1);
    sa += __shfl_xor_sync(0xffffffffu, sa, 2);
    sb += __shfl_xor_sync(0xffffffffu, sb, 2);
    float ma = sa * (-1.0f / C_IN), mb = sb * (-1.0f / C_IN);
    float va = 0.f, vb = 0.f;
#pragma unroll
    for (int i = 0; i < 24; i++) {
        xa[i] = fmaf(xa[i], dwf[i], ma);
        xb[i] = fmaf(xb[i], dwf[i], mb);
        va = fmaf(xa[i], xa[i], va);
        vb = fmaf(xb[i], xb[i], vb);
    }
    va += __shfl_xor_sync(0xffffffffu, va, 1);
    vb += __shfl_xor_sync(0xffffffffu, vb, 1);
    va += __shfl_xor_sync(0xffffffffu, va, 2);
    vb += __shfl_xor_sync(0xffffffffu, vb, 2);
    float ra = rsqrtf(va * (1.0f / C_IN) + 1e-5f) * GELU_KAPPA;
    float rb = rsqrtf(vb * (1.0f / C_IN) + 1e-5f) * GELU_KAPPA;
#pragma unroll
    for (int t = 0; t < 6; t++) {
#pragma unroll
        for (int h = 0; h < 2; h++) {
            int i = t * 4 + h * 2;
            f[t][2 * h] = pack_bf16(xa[i] * ra, xa[i + 1] * ra);
            f[t][2 * h + 1] = pack_bf16(xb[i] * rb, xb[i + 1] * rb);
        }
    }
}

__global__ void __launch_bounds__(NTHR2, 1)
k_main(const __grid_constant__ CUtensorMap tm_x, const __grid_constant__ CUtensorMap tm_w1,
       const __grid_constant__ CUtensorMap tm_out, const __grid_constant__ CUtensorMap tm_w2,
       const __nv_bfloat16* __restrict__ dw, const __nv_bfloat16* __restrict__ grn_g,
       const __nv_bfloat16* __restrict__ grn_b) {
    extern __shared__ __align__(1024) unsigned char smem[];
    unsigned char* s_w1 = smem;
    unsigned char* s_w2 = smem + 73728;
    unsigned char* s_x = smem + 2 * 73728;
    float* s_dw = reinterpret_cast<float*>(smem + 2 * 73728 + NWG2 * 2 * Y_TILE_BYTES);
    float* s_c = s_dw + 128;
    float* s_s = s_c + 128;
    float* s_tmp = s_s + C_H;
    uint64_t* s_bar = reinterpret_cast<uint64_t*>(s_tmp + 16);

    const int tid = threadIdx.x;
    const int wg = tid >> 7;
    const int warp = (tid >> 5) & 3;
    const int lane = tid & 31;
    const int q = lane & 3;
    const int nwg = gridDim.x * NWG2;
    int tile = blockIdx.x * NWG2 + wg;

    const uint32_t xbuf0 = smem_u32(s_x + wg * 2 * Y_TILE_BYTES);
    const uint32_t bar_x = smem_u32(s_bar + 1 + 2 * wg);
    if (tid == 0) {
        for (int i = 0; i < 1 + 2 * NWG2; i++) mbar_init(smem_u32(s_bar + i), 1);
        asm volatile("fence.mbarrier_init.release.cluster;\n" ::: "memory");
    }
    if (tid < C_IN) { s_dw[tid] = __bfloat162float(dw[tid]); s_c[tid] = 0.f; }
    __syncthreads();
    if (tid == 0) {
        mbar_expect_tx(smem_u32(s_bar), 6 * W1_BOX_BYTES + 73728);
        for (int i = 0; i < 6; i++) tma_load_2d(smem_u32(s_w1) + i * W1_BOX_BYTES, &tm_w1, smem_u32(s_bar), i * 64, 0);
        for (int g = 0; g < 12; g++)
            for (int i = 0; i < 3; i++)
                tma_load_2d(smem_u32(s_w2) + g * W2_SBO + i * 2048, &tm_w2, smem_u32(s_bar), g * 8, i * 128);
    }
    if ((tid & 127) == 0 && tile < NTILES) tma_x_tile(xbuf0, &tm_x, bar_x, tile);
    float gg[2];
    gg[0] = __bfloat162float(grn_g[tid]);
    gg[1] = (tid + NTHR2 < C_H) ? __bfloat162float(grn_g[tid + NTHR2]) : 0.f;
    asm volatile("griddepcontrol.wait;\n" ::: "memory");
    float lsum = 0.f;
    for (int k = tid; k < C_H; k += NTHR2) {
        float gx = sqrtf(__ldcg(&g_sum[k]) + 1e-6f);
        s_s[k] = gx;
        lsum += gx;
    }
#pragma unroll
    for (int o = 16; o > 0; o >>= 1) lsum += __shfl_xor_sync(0xffffffffu, lsum, o);
    if (lane == 0) s_tmp[tid >> 5] = lsum;
    __syncthreads();
    __shared__ unsigned int s_last;
    if (tid == 0) s_last = (atomicAdd(&g_done, 1u) == gridDim.x - 1);
    float tot = 0.f;
#pragma unroll
    for (int i = 0; i < NTHR2 / 32; i++) tot += s_tmp[i];
    float inv = 1.0f / (tot * (1.0f / C_H) + 1e-6f);
    {
        int j = 0;
        for (int k = tid; k < C_H; k += NTHR2, j++) s_s[k] = (0.5f / GELU_KAPPA) * (1.0f + gg[j] * (s_s[k] * inv));
    }
    __syncthreads();
    if (s_last) {
        for (int k = tid; k < C_H; k += NTHR2) g_sum[k] = 0.f;
        if (tid == 0) g_done = 0;
    }
    mbar_wait(smem_u32(s_bar), 0);
    if (tid < 252) {
        const int nc = tid % 12, k0 = tid / 12;
        float acc[8];
#pragma unroll
        for (int e = 0; e < 8; e++) acc[e] = 0.f;
        for (int k = k0; k < C_H; k += 21) {
            uint4* ptr = reinterpret_cast<uint4*>(s_w2 + nc * W2_SBO + k * 16);
            uint4 v = *ptr;
            float sk = s_s[k], b = __bfloat162float(grn_b[k]);
            float f0 = bf_lo(v.x), f1 = bf_hi(v.x), f2 = bf_lo(v.y), f3 = bf_hi(v.y);
            float f4 = bf_lo(v.z), f5 = bf_hi(v.z), f6 = bf_lo(v.w), f7 = bf_hi(v.w);
            acc[0] = fmaf(b, f0, acc[0]); acc[1] = fmaf(b, f1, acc[1]); acc[2] = fmaf(b, f2, acc[2]); acc[3] = fmaf(b, f3, acc[3]);
            acc[4] = fmaf(b, f4, acc[4]); acc[5] = fmaf(b, f5, acc[5]); acc[6] = fmaf(b, f6, acc[6]); acc[7] = fmaf(b, f7, acc[7]);
            uint4 o;
            o.x = pack_bf16(sk * f0, sk * f1); o.y = pack_bf16(sk * f2, sk * f3);
            o.z = pack_bf16(sk * f4, sk * f5); o.w = pack_bf16(sk * f6, sk * f7);
            *ptr = o;
        }
#pragma unroll
        for (int e = 0; e < 8; e++) atomicAdd(&s_c[nc * 8 + e], acc[e]);
    }
    proxy_fence();
    __syncthreads();

    const uint64_t w1_desc = make_desc(smem_u32(s_w1), W1_BOX_BYTES, 1024, 1);
    const uint64_t w2_desc = make_desc(smem_u32(s_w2), W2_LBO, W2_SBO, 0);
    const int lrow = warp * 16 + ((lane >> 3) & 1) * 8 + (lane & 7);
    const int lhalf = lane >> 4;
    const int lsw = (lrow >> 1) & 3;
    const uint32_t loff0 = lrow * 64 + (((0 + lhalf) ^ lsw) << 4);
    const uint32_t loff1 = lrow * 64 + (((2 + lhalf) ^ lsw) << 4);

    int it = 0;
    for (; tile < NTILES; tile += nwg, it++) {
        const int buf = it & 1;
        const uint32_t xb = xbuf0 + buf * Y_TILE_BYTES;
        if ((tid & 127) == 0 && tile + nwg < NTILES) {
            asm volatile("cp.async.bulk.wait_group.read 0;\n" ::: "memory");
            tma_x_tile(xbuf0 + (buf ^ 1) * Y_TILE_BYTES, &tm_x, bar_x + (buf ^ 1) * 8, tile + nwg);
        }
        mbar_wait(bar_x + buf * 8, (it >> 1) & 1);
        uint32_t f[6][4];
#pragma unroll
        for (int t = 0; t < 6; t++)
            ldsm_x4(xb + (t >> 1) * Y_BOX_BYTES + ((t & 1) ? loff1 : loff0), f[t][0], f[t][1], f[t][2], f[t][3]);
        ln_frag(f, s_dw + 2 * q);

        float O[48];
#pragma unroll
        for (int j = 0; j < 12; j++) {
            float2 cc = *reinterpret_cast<const float2*>(&s_c[8 * j + 2 * q]);
            O[4 * j] = cc.x; O[4 * j + 1] = cc.y; O[4 * j + 2] = cc.x; O[4 * j + 3] = cc.y;
        }
        float S[2][32];
        uint32_t hf[2][16];
        wg_fence();
#pragma unroll
        for (int t = 0; t < 6; t++) wgmma_rs_n64(S[0], f[t][0], f[t][1], f[t][2], f[t][3], w1_desc + ((t * 2048) >> 4), t != 0);
        wg_commit();
#pragma unroll
        for (int c = 0; c < 6; c++) {
            if (c + 1 < 6) {
                wg_fence();
#pragma unroll
                for (int t = 0; t < 6; t++)
                    wgmma_rs_n64(S[(c + 1) & 1], f[t][0], f[t][1], f[t][2], f[t][3],
                                 w1_desc + (((c + 1) * W1_BOX_BYTES + t * 2048) >> 4), t != 0);
                wg_commit();
                if (c == 0) wg_wait<1>(); else wg_wait<2>();
            } else {
                wg_wait<1>();
            }
            float(&Sc)[32] = S[c & 1];
            uint32_t(&h)[16] = hf[c & 1];
#pragma unroll
            for (int j = 0; j < 8; j++) {
                float g0 = gelu2(Sc[4 * j]);
                float g1 = gelu2(Sc[4 * j + 1]);
                float g2 = gelu2(Sc[4 * j + 2]);
                float g3 = gelu2(Sc[4 * j + 3]);
                h[2 * j] = pack_bf16(g0, g1);
                h[2 * j + 1] = pack_bf16(g2, g3);
            }
            wg_fence();
#pragma unroll
            for (int t = 0; t < 4; t++)
                wgmma_n96(O, h[4 * t], h[4 * t + 1], h[4 * t + 2], h[4 * t + 3],
                          w2_desc + (((c * 8 + 2 * t) * W2_LBO) >> 4));
            wg_commit();
        }
        uint32_t xr[6][4];
#pragma unroll
        for (int t = 0; t < 6; t++)
            ldsm_x4(xb + (t >> 1) * Y_BOX_BYTES + ((t & 1) ? loff1 : loff0), xr[t][0], xr[t][1], xr[t][2], xr[t][3]);
        wg_wait<0>();
#pragma unroll
        for (int t = 0; t < 6; t++) {
            uint32_t o0 = pack_bf16(bf_lo(xr[t][0]) + O[8 * t + 0], bf_hi(xr[t][0]) + O[8 * t + 1]);
            uint32_t o1 = pack_bf16(bf_lo(xr[t][1]) + O[8 * t + 2], bf_hi(xr[t][1]) + O[8 * t + 3]);
            uint32_t o2 = pack_bf16(bf_lo(xr[t][2]) + O[8 * t + 4], bf_hi(xr[t][2]) + O[8 * t + 5]);
            uint32_t o3 = pack_bf16(bf_lo(xr[t][3]) + O[8 * t + 6], bf_hi(xr[t][3]) + O[8 * t + 7]);
            stsm_x4(xb + (t >> 1) * Y_BOX_BYTES + ((t & 1) ? loff1 : loff0), o0, o1, o2, o3);
        }
        proxy_fence();
        wg_bar(1 + wg);
        if ((tid & 127) == 0) {
#pragma unroll
            for (int i = 0; i < 3; i++) tma_store_2d(&tm_out, xb + i * Y_BOX_BYTES, i * 32, tile * TILE_M);
            asm volatile("cp.async.bulk.commit_group;\n" ::: "memory");
        }
    }
    if ((tid & 127) == 0) asm volatile("cp.async.bulk.wait_group 0;\n" ::: "memory");
}

#define SMEM1 (73728 + NWG * 2 * Y_TILE_BYTES + 512 + 1536 + 128)
#define SMEM2 (2 * 73728 + NWG2 * 2 * Y_TILE_BYTES + 512 + 512 + 1536 + 64 + 64)

typedef CUresult (*PFN_encodeTiled)(CUtensorMap*, CUtensorMapDataType, cuuint32_t, void*, const cuuint64_t*, const cuuint64_t*,
                                    const cuuint32_t*, const cuuint32_t*, CUtensorMapInterleave, CUtensorMapSwizzle,
                                    CUtensorMapL2promotion, CUtensorMapFloatOOBfill);

extern "C" void kernel_launch(void* const* d_in, const int* in_sizes, int n_in, void* d_out, int out_size) {
    const __nv_bfloat16* x = (const __nv_bfloat16*)d_in[0];
    const __nv_bfloat16* dw = (const __nv_bfloat16*)d_in[1];
    const __nv_bfloat16* w1 = (const __nv_bfloat16*)d_in[2];
    const __nv_bfloat16* w2 = (const __nv_bfloat16*)d_in[3];
    const __nv_bfloat16* grn_g = (const __nv_bfloat16*)d_in[4];
    const __nv_bfloat16* grn_b = (const __nv_bfloat16*)d_in[5];

    static int n_sm = 0;
    static CUtensorMap tm_x, tm_w1, tm_out, tm_w2;
    static const void* last_x = nullptr;
    static const void* last_w1 = nullptr;
    static const void* last_out = nullptr;
    static const void* last_w2 = nullptr;
    static PFN_encodeTiled encode = nullptr;
    if (n_sm == 0) {
        int dev = 0;
        cudaGetDevice(&dev);
        cudaDeviceGetAttribute(&n_sm, cudaDevAttrMultiProcessorCount, dev);
        if (n_sm > MAX_CTAS) n_sm = MAX_CTAS;
        cudaFuncSetAttribute(k_stats, cudaFuncAttributeMaxDynamicSharedMemorySize, SMEM1);
        cudaFuncSetAttribute(k_main, cudaFuncAttributeMaxDynamicSharedMemorySize, SMEM2);
        cudaDriverEntryPointQueryResult qres;
        void* fn = nullptr;
        cudaGetDriverEntryPoint("cuTensorMapEncodeTiled", &fn, cudaEnableDefault, &qres);
        encode = (PFN_encodeTiled)fn;
    }
    if (last_x != x || last_w1 != w1 || last_out != d_out || last_w2 != w2) {
        cuuint64_t dims[2] = {96, (cuuint64_t)NROWS};
        cuuint64_t strides[1] = {192};
        cuuint32_t box[2] = {32, 64};
        cuuint32_t es[2] = {1, 1};
        encode(&tm_x, CU_TENSOR_MAP_DATA_TYPE_BFLOAT16, 2, (void*)x, dims, strides, box, es, CU_TENSOR_MAP_INTERLEAVE_NONE,
               CU_TENSOR_MAP_SWIZZLE_64B, CU_TENSOR_MAP_L2_PROMOTION_L2_128B, CU_TENSOR_MAP_FLOAT_OOB_FILL_NONE);
        encode(&tm_out, CU_TENSOR_MAP_DATA_TYPE_BFLOAT16, 2, d_out, dims, strides, box, es, CU_TENSOR_MAP_INTERLEAVE_NONE,
               CU_TENSOR_MAP_SWIZZLE_64B, CU_TENSOR_MAP_L2_PROMOTION_L2_128B, CU_TENSOR_MAP_FLOAT_OOB_FILL_NONE);
        cuuint64_t dimsw[2] = {384, 96};
        cuuint64_t stridesw[1] = {768};
        cuuint32_t boxw[2] = {64, 96};
        encode(&tm_w1, CU_TENSOR_MAP_DATA_TYPE_BFLOAT16, 2, (void*)w1, dimsw, stridesw, boxw, es, CU_TENSOR_MAP_INTERLEAVE_NONE,
               CU_TENSOR_MAP_SWIZZLE_128B, CU_TENSOR_MAP_L2_PROMOTION_L2_128B, CU_TENSOR_MAP_FLOAT_OOB_FILL_NONE);
        cuuint64_t dims2[2] = {96, 384};
        cuuint32_t box2[2] = {8, 128};
        encode(&tm_w2, CU_TENSOR_MAP_DATA_TYPE_BFLOAT16, 2, (void*)w2, dims2, strides, box2, es, CU_TENSOR_MAP_INTERLEAVE_NONE,
               CU_TENSOR_MAP_SWIZZLE_NONE, CU_TENSOR_MAP_L2_PROMOTION_L2_128B, CU_TENSOR_MAP_FLOAT_OOB_FILL_NONE);
        last_x = x;
        last_w1 = w1;
        last_out = d_out;
        last_w2 = w2;
    }
    k_stats<<<n_sm, NTHR, SMEM1>>>(tm_x, tm_w1, dw);
    cudaLaunchConfig_t cfg = {};
    cfg.gridDim = dim3(n_sm);
    cfg.blockDim = dim3(NTHR2);
    cfg.dynamicSmemBytes = SMEM2;
    cfg.stream = cudaStreamPerThread;
    cudaLaunchAttribute attr[1];
    attr[0].id = cudaLaunchAttributeProgrammaticStreamSerialization;
    attr[0].val.programmaticStreamSerializationAllowed = 1;
    cfg.attrs = attr;
    cfg.numAttrs = 1;
    cudaLaunchKernelEx(&cfg, k_main, tm_x, tm_w1, tm_out, tm_w2, dw, grn_g, grn_b);
}
```

```cpp
#include <cuda_runtime.h>
#include <cuda_bf16.h>
#include <stdint.h>
#include <cuda.h>

#define C_IN 96
#define C_H 384
#define NROWS (512 * 512)
#define TILE_M 64
#define NTILES (NROWS / TILE_M)
#define MAX_CTAS 256
#define NWG 4
#define NTHR (NWG * 128)

__device__ float g_sum[C_H];
__device__ unsigned int g_done;
__device__ __align__(1024) unsigned char g_w2img[73728];
__device__ float g_c[C_IN];
#define TSTAMP(i)

#define GELU_KAPPA 0.3292034911525734f
#define GELU_C0K 2.423681954311584f

__device__ __forceinline__ uint32_t smem_u32(const void* p) { return (uint32_t)__cvta_generic_to_shared(p); }
__device__ __forceinline__ uint64_t make_desc(uint32_t addr, uint32_t lbo, uint32_t sbo, uint32_t swz = 0) {
    uint64_t d = 0;
    d |= (uint64_t)((addr & 0x3FFFF) >> 4);
    d |= (uint64_t)((lbo >> 4) & 0x3FFF) << 16;
    d |= (uint64_t)((sbo >> 4) & 0x3FFF) << 32;
    d |= (uint64_t)swz << 62;
    return d;
}
__device__ __forceinline__ void mbar_init(uint32_t bar, uint32_t count) {
    asm volatile("mbarrier.init.shared::cta.b64 [%0], %1;\n" ::"r"(bar), "r"(count) : "memory");
}
__device__ __forceinline__ void mbar_expect_tx(uint32_t bar, uint32_t bytes) {
    asm volatile("mbarrier.arrive.expect_tx.shared::cta.b64 _, [%0], %1;\n" ::"r"(bar), "r"(bytes) : "memory");
}
__device__ __forceinline__ void mbar_wait(uint32_t bar, uint32_t parity) {
    asm volatile(
        "{\n.reg .pred p;\n"
        "WAIT_LOOP:\n"
        "mbarrier.try_wait.parity.shared::cta.b64 p, [%0], %1;\n"
        "@p bra WAIT_DONE;\n"
        "bra WAIT_LOOP;\n"
        "WAIT_DONE:\n}\n" ::"r"(bar), "r"(parity) : "memory");
}
__device__ __forceinline__ void tma_load_2d(uint32_t dst, const CUtensorMap* tm, uint32_t bar, int c0, int c1) {
    asm volatile(
        "cp.async.bulk.tensor.2d.shared::cluster.global.mbarrier::complete_tx::bytes [%0], [%1, {%3, %4}], [%2];\n" ::"r"(dst),
        "l"(reinterpret_cast<uint64_t>(tm)), "r"(bar), "r"(c0), "r"(c1)
        : "memory");
}
__device__ __forceinline__ void wg_fence() { asm volatile("wgmma.fence.sync.aligned;\n" ::: "memory"); }
__device__ __forceinline__ void wg_commit() { asm volatile("wgmma.commit_group.sync.aligned;\n" ::: "memory"); }
template <int N>
__device__ __forceinline__ void wg_wait() { asm volatile("wgmma.wait_group.sync.aligned %0;\n" ::"n"(N) : "memory"); }
__device__ __forceinline__ void wg_bar(int id) { asm volatile("bar.sync %0, 128;" ::"r"(id) : "memory"); }
__device__ __forceinline__ void proxy_fence() {
 asm volatile("fence.proxy.async.shared::cta;\n" ::: "memory"); }
__device__ __forceinline__ void cp_async16(uint32_t dst, const void* src) {
    asm volatile("cp.async.cg.shared.global [%0], [%1], 16;\n" ::"r"(dst), "l"(src) : "memory");
}
__device__ __forceinline__ void cp_async_commit() { asm volatile("cp.async.commit_group;\n" ::: "memory"); }
__device__ __forceinline__ void cp_async_wait_all() { asm volatile("cp.async.wait_group 0;\n" ::: "memory"); }
__device__ __forceinline__ void prefetch_l2(const void* p) { asm volatile("prefetch.global.L2 [%0];\n" ::"l"(p)); }

__device__ __forceinline__ float tanh_approx(float x) {
    float y;
    asm("tanh.approx.f32 %0, %1;" : "=f"(y) : "f"(x));
    return y;
}
__device__ __forceinline__ uint32_t pack_bf16(float lo, float hi) {
    uint32_t r;
    asm("cvt.rn.bf16x2.f32 %0, %1, %2;" : "=r"(r) : "f"(hi), "f"(lo));
    return r;
}
__device__ __forceinline__ float bf_lo(uint32_t v) { return __uint_as_float(v << 16); }
__device__ __forceinline__ float bf_hi(uint32_t v) { return __uint_as_float(v & 0xffff0000u); }

#define ACC32(d)                                                                                             \
    "+f"(d[0]), "+f"(d[1]), "+f"(d[2]), "+f"(d[3]), "+f"(d[4]), "+f"(d[5]), "+f"(d[6]), "+f"(d[7]),          \
        "+f"(d[8]), "+f"(d[9]), "+f"(d[10]), "+f"(d[11]), "+f"(d[12]), "+f"(d[13]), "+f"(d[14]), "+f"(d[15]), \
        "+f"(d[16]), "+f"(d[17]), "+f"(d[18]), "+f"(d[19]), "+f"(d[20]), "+f"(d[21]), "+f"(d[22]),           \
        "+f"(d[23]), "+f"(d[24]), "+f"(d[25]), "+f"(d[26]), "+f"(d[27]), "+f"(d[28]), "+f"(d[29]),           \
        "+f"(d[30]), "+f"(d[31])
#define ACC32_STR                                                                \
    "{%0, %1, %2, %3, %4, %5, %6, %7, %8, %9, %10, %11, %12, %13, %14, %15, "    \
    " %16, %17, %18, %19, %20, %21, %22, %23, %24, %25, %26, %27, %28, %29, %30, %31}"

__device__ __forceinline__ void wgmma_ss_n64_tA(float (&d)[32], uint64_t adesc, uint64_t bdesc, int scale_d) {
    asm volatile(
        "{\n.reg .pred p;\nsetp.ne.b32 p, %34, 0;\n"
        "wgmma.mma_async.sync.aligned.m64n64k16.f32.bf16.bf16 " ACC32_STR ", %32, %33, p, 1, 1, 1, 0;\n}\n"
        : ACC32(d)
        : "l"(adesc), "l"(bdesc), "r"(scale_d));
}
__device__ __forceinline__ void wgmma_ss_n64(float (&d)[32], uint64_t adesc, uint64_t bdesc, int scale_d) {
    asm volatile(
        "{\n.reg .pred p;\nsetp.ne.b32 p, %34, 0;\n"
        "wgmma.mma_async.sync.aligned.m64n64k16.f32.bf16.bf16 " ACC32_STR ", %32, %33, p, 1, 1, 0, 1;\n}\n"
        : ACC32(d)
        : "l"(adesc), "l"(bdesc), "r"(scale_d));
}
__device__ __forceinline__ void wgmma_n96(float (&d)[48], uint32_t a0, uint32_t a1, uint32_t a2, uint32_t a3,
                                          uint64_t bdesc) {
    asm volatile(
        "{\n"
        "wgmma.mma_async.sync.aligned.m64n96k16.f32.bf16.bf16 "
        "{%0, %1, %2, %3, %4, %5, %6, %7, %8, %9, %10, %11, %12, %13, %14, %15, "
        " %16, %17, %18, %19, %20, %21, %22, %23, %24, %25, %26, %27, %28, %29, %30, %31, "
        " %32, %33, %34, %35, %36, %37, %38, %39, %40, %41, %42, %43, %44, %45, %46, %47}, "
        "{%48, %49, %50, %51}, %52, 1, 1, 1, 1;\n"
        "}\n"
        : ACC32(d), "+f"(d[32]), "+f"(d[33]), "+f"(d[34]), "+f"(d[35]), "+f"(d[36]), "+f"(d[37]), "+f"(d[38]),
          "+f"(d[39]), "+f"(d[40]), "+f"(d[41]), "+f"(d[42]), "+f"(d[43]), "+f"(d[44]), "+f"(d[45]), "+f"(d[46]),
          "+f"(d[47])
        : "r"(a0), "r"(a1), "r"(a2), "r"(a3), "l"(bdesc));
}

#define W2_LBO 128
#define W2_SBO (48 * 128)
#define W1_BOX_BYTES (96 * 128)
#define Y_BOX_BYTES (64 * 64)
#define Y_TILE_BYTES (3 * Y_BOX_BYTES)

__device__ __forceinline__ void ln_row4(const uint4 (&xv)[3], const float* __restrict__ s_dwq, uint4 (&y)[3]) {
    float xf[24], dwf[24];
    float s = 0.f;
#pragma unroll
    for (int i = 0; i < 3; i++) {
        uint32_t w[4] = {xv[i].x, xv[i].y, xv[i].z, xv[i].w};
        float4 da = *reinterpret_cast<const float4*>(s_dwq + 32 * i);
        float4 db = *reinterpret_cast<const float4*>(s_dwq + 32 * i + 4);
        dwf[i * 8 + 0] = da.x; dwf[i * 8 + 1] = da.y; dwf[i * 8 + 2] = da.z; dwf[i * 8 + 3] = da.w;
        dwf[i * 8 + 4] = db.x; dwf[i * 8 + 5] = db.y; dwf[i * 8 + 6] = db.z; dwf[i * 8 + 7] = db.w;
#pragma unroll
        for (int p = 0; p < 4; p++) {
            xf[i * 8 + 2 * p] = bf_lo(w[p]);
            xf[i * 8 + 2 * p + 1] = bf_hi(w[p]);
        }
#pragma unroll
        for (int p = 0; p < 8; p++) s = fmaf(xf[i * 8 + p], dwf[i * 8 + p], s);
    }
    s += __shfl_xor_sync(0xffffffffu, s, 1);
    s += __shfl_xor_sync(0xffffffffu, s, 2);
    float nmean = s * (-1.0f / C_IN);
    float v = 0.f;
#pragma unroll
    for (int i = 0; i < 24; i++) {
        xf[i] = fmaf(xf[i], dwf[i], nmean);
        v = fmaf(xf[i], xf[i], v);
    }
    v += __shfl_xor_sync(0xffffffffu, v, 1);
    v += __shfl_xor_sync(0xffffffffu, v, 2);
    float rstd = rsqrtf(v * (1.0f / C_IN) + 1e-5f) * GELU_KAPPA;
#pragma unroll
    for (int i = 0; i < 3; i++) {
        y[i].x = pack_bf16(xf[i * 8 + 0] * rstd, xf[i * 8 + 1] * rstd);
        y[i].y = pack_bf16(xf[i * 8 + 2] * rstd, xf[i * 8 + 3] * rstd);
        y[i].z = pack_bf16(xf[i * 8 + 4] * rstd, xf[i * 8 + 5] * rstd);
        y[i].w = pack_bf16(xf[i * 8 + 6] * rstd, xf[i * 8 + 7] * rstd);
    }
}

__device__ __forceinline__ void ln_tile_inplace(unsigned char* yp, const float* __restrict__ s_dwq) {
    uint4 xv[3], y[3];
#pragma unroll
    for (int i = 0; i < 3; i++) xv[i] = *reinterpret_cast<const uint4*>(yp + i * Y_BOX_BYTES);
    ln_row4(xv, s_dwq, y);
#pragma unroll
    for (int i = 0; i < 3; i++) *reinterpret_cast<uint4*>(yp + i * Y_BOX_BYTES) = y[i];
#pragma unroll
    for (int i = 0; i < 3; i++) xv[i] = *reinterpret_cast<const uint4*>(yp + 512 + i * Y_BOX_BYTES);
    ln_row4(xv, s_dwq, y);
#pragma unroll
    for (int i = 0; i < 3; i++) *reinterpret_cast<uint4*>(yp + 512 + i * Y_BOX_BYTES) = y[i];
}

__device__ __forceinline__ float gelu2(float u) {
    float t = fmaf(u, u, GELU_C0K);
    float a = t * u;
    float th = tanh_approx(a);
    return fmaf(u, th, u);
}

__device__ __forceinline__ void tma_x_tile(uint32_t dst, const CUtensorMap* tmx, uint32_t bar, int tile) {
    mbar_expect_tx(bar, Y_TILE_BYTES);
#pragma unroll
    for (int i = 0; i < 3; i++) tma_load_2d(dst + i * Y_BOX_BYTES, tmx, bar, i * 32, tile * TILE_M);
}

__global__ void __launch_bounds__(NTHR, 1)
k_stats(const __grid_constant__ CUtensorMap tm_x, const __grid_constant__ CUtensorMap tm_w1,
        const __nv_bfloat16* __restrict__ dw, const __nv_bfloat16* __restrict__ w2,
        const __nv_bfloat16* __restrict__ grn_g, const __nv_bfloat16* __restrict__ grn_b) {
    extern __shared__ __align__(1024) unsigned char smem[];
    unsigned char* s_w1 = smem;
    unsigned char* s_y = smem + 73728;
    float* s_dw = reinterpret_cast<float*>(smem + 73728 + NWG * 2 * Y_TILE_BYTES);
    float* s_red = s_dw + 128;
    uint64_t* s_bar = reinterpret_cast<uint64_t*>(s_red + C_H);

    const int tid = threadIdx.x;
    const int wg = tid >> 7;
    const int warp = (tid >> 5) & 3;
    const int lane = tid & 31;
    const int q = lane & 3;
    const int nwg = gridDim.x * NWG;
    int tile = blockIdx.x * NWG + wg;

    if (tid == 0) {
        for (int i = 0; i < 1 + 2 * NWG; i++) mbar_init(smem_u32(s_bar + i), 1);
        asm volatile("fence.mbarrier_init.release.cluster;\n" ::: "memory");
    }
    if (tid < C_IN) s_dw[tid] = __bfloat162float(dw[tid]);
    for (int i = tid; i < C_H; i += NTHR) s_red[i] = 0.f;
    __syncthreads();
    const uint32_t ybuf0 = smem_u32(s_y + wg * 2 * Y_TILE_BYTES);
    const uint32_t bar_y = smem_u32(s_bar + 1 + 2 * wg);
    if (tid == 0) {
        mbar_expect_tx(smem_u32(s_bar), 6 * W1_BOX_BYTES);
        for (int i = 0; i < 6; i++) tma_load_2d(smem_u32(s_w1) + i * W1_BOX_BYTES, &tm_w1, smem_u32(s_bar), i * 64, 0);
    }
    if ((tid & 127) == 0 && tile < NTILES) tma_x_tile(ybuf0, &tm_x, bar_y, tile);

    asm volatile("griddepcontrol.launch_dependents;\n" ::: "memory");
    if (blockIdx.x == 0) {
        prefetch_l2(reinterpret_cast<const unsigned char*>(w2) + tid * 128);
        if (tid < 64) prefetch_l2(reinterpret_cast<const unsigned char*>(w2) + (512 + tid) * 128);
    }
    float ss[12];
#pragma unroll
    for (int i = 0; i < 12; i++) ss[i] = 0.f;

    const uint64_t w1_desc = make_desc(smem_u32(s_w1), W1_BOX_BYTES, 1024, 1);
    const int rl = warp * 16 + (lane >> 2);
    const int yoff = rl * 64 + ((q ^ ((rl >> 1) & 3)) * 16);
    mbar_wait(smem_u32(s_bar), 0);

    int it = 0;
    for (; tile < NTILES; tile += nwg, it++) {
        const int buf = it & 1;
        if ((tid & 127) == 0 && tile + nwg < NTILES) tma_x_tile(ybuf0 + (buf ^ 1) * Y_TILE_BYTES, &tm_x, bar_y + (buf ^ 1) * 8, tile + nwg);
        mbar_wait(bar_y + buf * 8, (it >> 1) & 1);
        unsigned char* ytile = s_y + (wg * 2 + buf) * Y_TILE_BYTES;
        ln_tile_inplace(ytile + yoff, s_dw + 8 * q);
        proxy_fence();
        wg_bar(1 + wg);
        const uint64_t y_desc = make_desc(smem_u32(ytile), 16, 512, 2);
        float S[2][32];
        wg_fence();
#pragma unroll
        for (int t = 0; t < 6; t++)
            wgmma_ss_n64_tA(S[0], w1_desc + ((t * 2048) >> 4), y_desc + (((t >> 1) * Y_BOX_BYTES + (t & 1) * 32) >> 4), t != 0);
        wg_commit();
#pragma unroll
        for (int m = 0; m < 6; m++) {
            if (m + 1 < 6) {
                wg_fence();
#pragma unroll
                for (int t = 0; t < 6; t++)
                    wgmma_ss_n64_tA(S[(m + 1) & 1], w1_desc + (((m + 1) * W1_BOX_BYTES + t * 2048) >> 4),
                                    y_desc + (((t >> 1) * Y_BOX_BYTES + (t & 1) * 32) >> 4), t != 0);
                wg_commit();
                wg_wait<1>();
            } else {
                wg_wait<0>();
            }
            float(&Sc)[32] = S[m & 1];
            float a0 = ss[2 * m], a1 = ss[2 * m + 1];
#pragma unroll
            for (int j = 0; j < 8; j++) {
                float g0 = gelu2(Sc[4 * j]);
                float g1 = gelu2(Sc[4 * j + 1]);
                float g2 = gelu2(Sc[4 * j + 2]);
                float g3 = gelu2(Sc[4 * j + 3]);
                a0 = fmaf(g0, g0, a0);
                a1 = fmaf(g2, g2, a1);
                a0 = fmaf(g1, g1, a0);
                a1 = fmaf(g3, g3, a1);
            }
            ss[2 * m] = a0;
            ss[2 * m + 1] = a1;
        }
        wg_bar(1 + wg);
    }
#pragma unroll
    for (int i = 0; i < 12; i++) {
        float v = ss[i];
        v += __shfl_xor_sync(0xffffffffu, v, 1);
        v += __shfl_xor_sync(0xffffffffu, v, 2);
        if (q == 0) {
            int m = i >> 1, hh = i & 1;
            atomicAdd(&s_red[m * 64 + warp * 16 + hh * 8 + (lane >> 2)], v);
        }
    }
    __syncthreads();
    const float sc = 0.25f / (GELU_KAPPA * GELU_KAPPA);
    for (int i = tid; i < C_H; i += NTHR) atomicAdd(&g_sum[i], s_red[i] * sc);
    __threadfence();
    __syncthreads();
    __shared__ unsigned int s_last;
    if (tid == 0) s_last = (atomicAdd(&g_done, 1u) == gridDim.x - 1);
    __syncthreads();
    if (!s_last) return;
    __threadfence();
    uint4 w2v[384 * 12 / NTHR];
#pragma unroll
    for (int i = 0; i < 384 * 12 / NTHR; i++) {
        int it2 = tid + i * NTHR;
        int kr = it2 & 7;
        int nb = (it2 >> 3) % 12;
        int kb = (it2 >> 3) / 12;
        w2v[i] = __ldg(reinterpret_cast<const uint4*>(w2 + (kb * 8 + kr) * C_IN + nb * 8));
    }
    float* s_s = s_red;
    float* s_tmp = s_dw;
    float lsum = 0.f;
    if (tid < C_H) {
        float gx = sqrtf(__ldcg(&g_sum[tid]) + 1e-6f);
        g_sum[tid] = 0.f;
        s_s[tid] = gx;
        lsum = gx;
    }
#pragma unroll
    for (int o = 16; o > 0; o >>= 1) lsum += __shfl_xor_sync(0xffffffffu, lsum, o);
    if (lane == 0) s_tmp[tid >> 5] = lsum;
    if (tid == 0) g_done = 0;
    __syncthreads();
    float tot = 0.f;
#pragma unroll
    for (int i = 0; i < NTHR / 32; i++) tot += s_tmp[i];
    float inv = 1.0f / (tot * (1.0f / C_H) + 1e-6f);
    __syncthreads();
    if (tid < C_H) s_s[tid] = (0.5f / GELU_KAPPA) * (1.0f + __bfloat162float(grn_g[tid]) * (s_s[tid] * inv));
    if (tid < C_IN) s_tmp[tid] = 0.f;
    __syncthreads();
    {
        float a0 = 0.f, a1 = 0.f, a2 = 0.f;
        int kbase = (tid >> 5) * (C_H / (NTHR / 32));
#pragma unroll
        for (int k = kbase; k < kbase + C_H / (NTHR / 32); k++) {
            float b = __bfloat162float(grn_b[k]);
            a0 = fmaf(b, __bfloat162float(w2[k * C_IN + lane]), a0);
            a1 = fmaf(b, __bfloat162float(w2[k * C_IN + lane + 32]), a1);
            a2 = fmaf(b, __bfloat162float(w2[k * C_IN + lane + 64]), a2);
        }
        atomicAdd(&s_tmp[lane], a0);
        atomicAdd(&s_tmp[lane + 32], a1);
        atomicAdd(&s_tmp[lane + 64], a2);
    }
#pragma unroll
    for (int i = 0; i < 384 * 12 / NTHR; i++) {
        int it2 = tid + i * NTHR;
        int kr = it2 & 7;
        int nb = (it2 >> 3) % 12;
        int kb = (it2 >> 3) / 12;
        float sk = s_s[kb * 8 + kr];
        uint4 v = w2v[i];
        uint4 o;
        o.x = pack_bf16(sk * bf_lo(v.x), sk * bf_hi(v.x));
        o.y = pack_bf16(sk * bf_lo(v.y), sk * bf_hi(v.y));
        o.z = pack_bf16(sk * bf_lo(v.z), sk * bf_hi(v.z));
        o.w = pack_bf16(sk * bf_lo(v.w), sk * bf_hi(v.w));
        *reinterpret_cast<uint4*>(g_w2img + nb * W2_SBO + kb * W2_LBO + kr * 16) = o;
    }
    __syncthreads();
    if (tid < C_IN) g_c[tid] = s_tmp[tid];
}

#define NWG2 3
#define NTHR2 (NWG2 * 128)

__device__ __forceinline__ void wgmma_rs_n64(float (&d)[32], uint32_t a0, uint32_t a1, uint32_t a2, uint32_t a3,
                                             uint64_t bdesc, int scale_d) {
    asm volatile(
        "{\n.reg .pred p;\nsetp.ne.b32 p, %37, 0;\n"
        "wgmma.mma_async.sync.aligned.m64n64k16.f32.bf16.bf16 " ACC32_STR ", {%32, %33, %34, %35}, %36, p, 1, 1, 1;\n}\n"
        : ACC32(d)
        : "r"(a0), "r"(a1), "r"(a2), "r"(a3), "l"(bdesc), "r"(scale_d));
}
__device__ __forceinline__ void ldsm_x4(uint32_t addr, uint32_t& r0, uint32_t& r1, uint32_t& r2, uint32_t& r3) {
    asm volatile("ldmatrix.sync.aligned.m8n8.x4.shared.b16 {%0, %1, %2, %3}, [%4];\n"
                 : "=r"(r0), "=r"(r1), "=r"(r2), "=r"(r3) : "r"(addr) : "memory");
}
__device__ __forceinline__ void stsm_x4(uint32_t addr, uint32_t r0, uint32_t r1, uint32_t r2, uint32_t r3) {
    asm volatile("stmatrix.sync.aligned.m8n8.x4.shared.b16 [%0], {%1, %2, %3, %4};\n" ::"r"(addr), "r"(r0), "r"(r1), "r"(r2),
                 "r"(r3) : "memory");
}
__device__ __forceinline__ void tma_store_2d(const CUtensorMap* tm, uint32_t src, int c0, int c1) {
    asm volatile("cp.async.bulk.tensor.2d.global.shared::cta.bulk_group [%0, {%2, %3}], [%1];\n" ::"l"(
                     reinterpret_cast<uint64_t>(tm)), "r"(src), "r"(c0), "r"(c1) : "memory");
}

__device__ __forceinline__ void ln_frag(uint32_t (&f)[6][4], const float* __restrict__ s_dwq) {
    float xa[24], xb[24], dwf[24];
    float sa = 0.f, sb = 0.f;
#pragma unroll
    for (int t = 0; t < 6; t++) {
#pragma unroll
        for (int h = 0; h < 2; h++) {
            float2 d = *reinterpret_cast<const float2*>(s_dwq + 16 * t + 8 * h);
            int i = t * 4 + h * 2;
            dwf[i] = d.x; dwf[i + 1] = d.y;
            xa[i] = bf_lo(f[t][2 * h]); xa[i + 1] = bf_hi(f[t][2 * h]);
            xb[i] = bf_lo(f[t][2 * h + 1]); xb[i + 1] = bf_hi(f[t][2 * h + 1]);
            sa = fmaf(xa[i], d.x, sa); sa = fmaf(xa[i + 1], d.y, sa);
            sb = fmaf(xb[i], d.x, sb); sb = fmaf(xb[i + 1], d.y, sb);
        }
    }
    sa += __shfl_xor_sync(0xffffffffu, sa, 1);
    sb += __shfl_xor_sync(0xffffffffu, sb, 1);
    sa += __shfl_xor_sync(0xffffffffu, sa, 2);
    sb += __shfl_xor_sync(0xffffffffu, sb, 2);
    float ma = sa * (-1.0f / C_IN), mb = sb * (-1.0f / C_IN);
    float va = 0.f, vb = 0.f;
#pragma unroll
    for (int i = 0; i < 24; i++) {
        xa[i] = fmaf(xa[i], dwf[i], ma);
        xb[i] = fmaf(xb[i], dwf[i], mb);
        va = fmaf(xa[i], xa[i], va);
        vb = fmaf(xb[i], xb[i], vb);
    }
    va += __shfl_xor_sync(0xffffffffu, va, 1);
    vb += __shfl_xor_sync(0xffffffffu, vb, 1);
    va += __shfl_xor_sync(0xffffffffu, va, 2);
    vb += __shfl_xor_sync(0xffffffffu, vb, 2);
    float ra = rsqrtf(va * (1.0f / C_IN) + 1e-5f) * GELU_KAPPA;
    float rb = rsqrtf(vb * (1.0f / C_IN) + 1e-5f) * GELU_KAPPA;
#pragma unroll
    for (int t = 0; t < 6; t++) {
#pragma unroll
        for (int h = 0; h < 2; h++) {
            int i = t * 4 + h * 2;
            f[t][2 * h] = pack_bf16(xa[i] * ra, xa[i + 1] * ra);
            f[t][2 * h + 1] = pack_bf16(xb[i] * rb, xb[i + 1] * rb);
        }
    }
}

__global__ void __launch_bounds__(NTHR2, 1)
k_main(const __grid_constant__ CUtensorMap tm_x, const __grid_constant__ CUtensorMap tm_w1,
       const __grid_constant__ CUtensorMap tm_out, const __nv_bfloat16* __restrict__ dw) {
    extern __shared__ __align__(1024) unsigned char smem[];
    unsigned char* s_w1 = smem;
    unsigned char* s_w2 = smem + 73728;
    unsigned char* s_x = smem + 2 * 73728;
    float* s_dw = reinterpret_cast<float*>(smem + 2 * 73728 + NWG2 * 2 * Y_TILE_BYTES);
    float* s_c = s_dw + 128;
    uint64_t* s_bar = reinterpret_cast<uint64_t*>(s_c + 128);

    const int tid = threadIdx.x;
    const int wg = tid >> 7;
    const int warp = (tid >> 5) & 3;
    const int lane = tid & 31;
    const int q = lane & 3;
    const int nwg = gridDim.x * NWG2;
    int tile = blockIdx.x * NWG2 + wg;

    const uint32_t xbuf0 = smem_u32(s_x + wg * 2 * Y_TILE_BYTES);
    const uint32_t bar_x = smem_u32(s_bar + 1 + 2 * wg);
    if (tid == 0) {
        for (int i = 0; i < 1 + 2 * NWG2; i++) mbar_init(smem_u32(s_bar + i), 1);
        asm volatile("fence.mbarrier_init.release.cluster;\n" ::: "memory");
    }
    if (tid < C_IN) s_dw[tid] = __bfloat162float(dw[tid]);
    __syncthreads();
    if ((tid & 127) == 0 && tile < NTILES) tma_x_tile(xbuf0, &tm_x, bar_x, tile);
    if (tid == 0) {
        mbar_expect_tx(smem_u32(s_bar), 6 * W1_BOX_BYTES + 73728);
        for (int i = 0; i < 6; i++) tma_load_2d(smem_u32(s_w1) + i * W1_BOX_BYTES, &tm_w1, smem_u32(s_bar), i * 64, 0);
    }
    asm volatile("griddepcontrol.wait;\n" ::: "memory");
    if (tid < C_IN) s_c[tid] = __ldcg(&g_c[tid]);
    if (tid == 0) {
        for (int i = 0; i < 6; i++)
            asm volatile("cp.async.bulk.shared::cluster.global.mbarrier::complete_tx::bytes [%0], [%1], %2, [%3];\n" ::"r"(
                             smem_u32(s_w2) + i * 12288),
                         "l"(g_w2img + i * 12288), "r"(12288), "r"(smem_u32(s_bar))
                         : "memory");
    }
    __syncthreads();
    mbar_wait(smem_u32(s_bar), 0);

    const uint64_t w1_desc = make_desc(smem_u32(s_w1), W1_BOX_BYTES, 1024, 1);
    const uint64_t w2_desc = make_desc(smem_u32(s_w2), W2_LBO, W2_SBO, 0);
    const int lrow = warp * 16 + ((lane >> 3) & 1) * 8 + (lane & 7);
    const int lhalf = lane >> 4;
    const int lsw = (lrow >> 1) & 3;
    const uint32_t loff0 = lrow * 64 + (((0 + lhalf) ^ lsw) << 4);
    const uint32_t loff1 = lrow * 64 + (((2 + lhalf) ^ lsw) << 4);

    int it = 0;
    for (; tile < NTILES; tile += nwg, it++) {
        const int buf = it & 1;
        const uint32_t xb = xbuf0 + buf * Y_TILE_BYTES;
        if ((tid & 127) == 0 && tile + nwg < NTILES) {
            asm volatile("cp.async.bulk.wait_group.read 0;\n" ::: "memory");
            tma_x_tile(xbuf0 + (buf ^ 1) * Y_TILE_BYTES, &tm_x, bar_x + (buf ^ 1) * 8, tile + nwg);
        }
        mbar_wait(bar_x + buf * 8, (it >> 1) & 1);
        uint32_t f[6][4];
#pragma unroll
        for (int t = 0; t < 6; t++)
            ldsm_x4(xb + (t >> 1) * Y_BOX_BYTES + ((t & 1) ? loff1 : loff0), f[t][0], f[t][1], f[t][2], f[t][3]);
        ln_frag(f, s_dw + 2 * q);

        float O[48];
#pragma unroll
        for (int j = 0; j < 12; j++) {
            float2 cc = *reinterpret_cast<const float2*>(&s_c[8 * j + 2 * q]);
            O[4 * j] = cc.x; O[4 * j + 1] = cc.y; O[4 * j + 2] = cc.x; O[4 * j + 3] = cc.y;
        }
        float S[32];
        uint32_t hf[16];
        wg_fence();
#pragma unroll
        for (int t = 0; t < 6; t++) wgmma_rs_n64(S, f[t][0], f[t][1], f[t][2], f[t][3], w1_desc + ((t * 2048) >> 4), t != 0);
        wg_commit();
#pragma unroll
        for (int c = 0; c < 6; c++) {
            wg_wait<0>();
#pragma unroll
            for (int j = 0; j < 8; j++) {
                float g0 = gelu2(S[4 * j]);
                float g1 = gelu2(S[4 * j + 1]);
                float g2 = gelu2(S[4 * j + 2]);
                float g3 = gelu2(S[4 * j + 3]);
                hf[2 * j] = pack_bf16(g0, g1);
                hf[2 * j + 1] = pack_bf16(g2, g3);
            }
            wg_fence();
#pragma unroll
            for (int t = 0; t < 4; t++)
                wgmma_n96(O, hf[4 * t], hf[4 * t + 1], hf[4 * t + 2], hf[4 * t + 3],
                          w2_desc + (((c * 8 + 2 * t) * W2_LBO) >> 4));
            if (c + 1 < 6) {
#pragma unroll
                for (int t = 0; t < 6; t++)
                    wgmma_rs_n64(S, f[t][0], f[t][1], f[t][2], f[t][3],
                                 w1_desc + (((c + 1) * W1_BOX_BYTES + t * 2048) >> 4), t != 0);
            }
            wg_commit();
        }
        uint32_t xr[6][4];
#pragma unroll
        for (int t = 0; t < 6; t++)
            ldsm_x4(xb + (t >> 1) * Y_BOX_BYTES + ((t & 1) ? loff1 : loff0), xr[t][0], xr[t][1], xr[t][2], xr[t][3]);
        wg_wait<0>();
#pragma unroll
        for (int t = 0; t < 6; t++) {
            uint32_t o0 = pack_bf16(bf_lo(xr[t][0]) + O[8 * t + 0], bf_hi(xr[t][0]) + O[8 * t + 1]);
            uint32_t o1 = pack_bf16(bf_lo(xr[t][1]) + O[8 * t + 2], bf_hi(xr[t][1]) + O[8 * t + 3]);
            uint32_t o2 = pack_bf16(bf_lo(xr[t][2]) + O[8 * t + 4], bf_hi(xr[t][2]) + O[8 * t + 5]);
            uint32_t o3 = pack_bf16(bf_lo(xr[t][3]) + O[8 * t + 6], bf_hi(xr[t][3]) + O[8 * t + 7]);
            stsm_x4(xb + (t >> 1) * Y_BOX_BYTES + ((t & 1) ? loff1 : loff0), o0, o1, o2, o3);
        }
        proxy_fence();
        wg_bar(1 + wg);
        if ((tid & 127) == 0) {
#pragma unroll
            for (int i = 0; i < 3; i++) tma_store_2d(&tm_out, xb + i * Y_BOX_BYTES, i * 32, tile * TILE_M);
            asm volatile("cp.async.bulk.commit_group;\n" ::: "memory");
        }
    }
    if ((tid & 127) == 0) asm volatile("cp.async.bulk.wait_group 0;\n" ::: "memory");
}

#define SMEM1 (73728 + NWG * 2 * Y_TILE_BYTES + 512 + 1536 + 128)
#define SMEM2 (2 * 73728 + NWG2 * 2 * Y_TILE_BYTES + 512 + 512 + 64)

typedef CUresult (*PFN_encodeTiled)(CUtensorMap*, CUtensorMapDataType, cuuint32_t, void*, const cuuint64_t*, const cuuint64_t*,
                                    const cuuint32_t*, const cuuint32_t*, CUtensorMapInterleave, CUtensorMapSwizzle,
                                    CUtensorMapL2promotion, CUtensorMapFloatOOBfill);

extern "C" void kernel_launch(void* const* d_in, const int* in_sizes, int n_in, void* d_out, int out_size) {
    const __nv_bfloat16* x = (const __nv_bfloat16*)d_in[0];
    const __nv_bfloat16* dw = (const __nv_bfloat16*)d_in[1];
    const __nv_bfloat16* w1 = (const __nv_bfloat16*)d_in[2];
    const __nv_bfloat16* w2 = (const __nv_bfloat16*)d_in[3];
    const __nv_bfloat16* grn_g = (const __nv_bfloat16*)d_in[4];
    const __nv_bfloat16* grn_b = (const __nv_bfloat16*)d_in[5];

    static int n_sm = 0;
    static CUtensorMap tm_x, tm_w1, tm_out;
    static const void* last_x = nullptr;
    static const void* last_w1 = nullptr;
    static const void* last_out = nullptr;
    static PFN_encodeTiled encode = nullptr;
    if (n_sm == 0) {
        int dev = 0;
        cudaGetDevice(&dev);
        cudaDeviceGetAttribute(&n_sm, cudaDevAttrMultiProcessorCount, dev);
        if (n_sm > MAX_CTAS) n_sm = MAX_CTAS;
        cudaFuncSetAttribute(k_stats, cudaFuncAttributeMaxDynamicSharedMemorySize, SMEM1);
        cudaFuncSetAttribute(k_main, cudaFuncAttributeMaxDynamicSharedMemorySize, SMEM2);
        cudaDriverEntryPointQueryResult qres;
        void* fn = nullptr;
        cudaGetDriverEntryPoint("cuTensorMapEncodeTiled", &fn, cudaEnableDefault, &qres);
        encode = (PFN_encodeTiled)fn;
    }
    if (last_x != x || last_w1 != w1 || last_out != d_out) {
        cuuint64_t dims[2] = {96, (cuuint64_t)NROWS};
        cuuint64_t strides[1] = {192};
        cuuint32_t box[2] = {32, 64};
        cuuint32_t es[2] = {1, 1};
        encode(&tm_x, CU_TENSOR_MAP_DATA_TYPE_BFLOAT16, 2, (void*)x, dims, strides, box, es, CU_TENSOR_MAP_INTERLEAVE_NONE,
               CU_TENSOR_MAP_SWIZZLE_64B, CU_TENSOR_MAP_L2_PROMOTION_L2_128B, CU_TENSOR_MAP_FLOAT_OOB_FILL_NONE);
        encode(&tm_out, CU_TENSOR_MAP_DATA_TYPE_BFLOAT16, 2, d_out, dims, strides, box, es, CU_TENSOR_MAP_INTERLEAVE_NONE,
               CU_TENSOR_MAP_SWIZZLE_64B, CU_TENSOR_MAP_L2_PROMOTION_L2_128B, CU_TENSOR_MAP_FLOAT_OOB_FILL_NONE);
        cuuint64_t dimsw[2] = {384, 96};
        cuuint64_t stridesw[1] = {768};
        cuuint32_t boxw[2] = {64, 96};
        encode(&tm_w1, CU_TENSOR_MAP_DATA_TYPE_BFLOAT16, 2, (void*)w1, dimsw, stridesw, boxw, es, CU_TENSOR_MAP_INTERLEAVE_NONE,
               CU_TENSOR_MAP_SWIZZLE_128B, CU_TENSOR_MAP_L2_PROMOTION_L2_128B, CU_TENSOR_MAP_FLOAT_OOB_FILL_NONE);
        last_x = x;
        last_w1 = w1;
        last_out = d_out;
    }
    k_stats<<<n_sm, NTHR, SMEM1>>>(tm_x, tm_w1, dw, w2, grn_g, grn_b);
    cudaLaunchConfig_t cfg = {};
    cfg.gridDim = dim3(n_sm);
    cfg.blockDim = dim3(NTHR2);
    cfg.dynamicSmemBytes = SMEM2;
    cfg.stream = cudaStreamPerThread;
    cudaLaunchAttribute attr[1];
    attr[0].id = cudaLaunchAttributeProgrammaticStreamSerialization;
    attr[0].val.programmaticStreamSerializationAllowed = 1;
    cfg.attrs = attr;
    cfg.numAttrs = 1;
    cudaLaunchKernelEx(&cfg, k_main, tm_x, tm_w1, tm_out, dw);
}
```

```cpp
#include <cuda_runtime.h>
#include <cuda_bf16.h>
#include <stdint.h>
#include <cuda.h>

#define C_IN 96
#define C_H 384
#define NROWS (512 * 512)
#define TILE_M 64
#define NTILES (NROWS / TILE_M)
#define MAX_CTAS 256
#define NWG 4
#define NTHR (NWG * 128)

__device__ float g_sum[C_H];
__device__ unsigned int g_done;
__device__ __align__(1024) unsigned char g_w2img[73728];
__device__ float g_c[C_IN];
#define TSTAMP(i)

#define GELU_KAPPA 0.3292034911525734f
#define GELU_C0K 2.423681954311584f

__device__ __forceinline__ uint32_t smem_u32(const void* p) { return (uint32_t)__cvta_generic_to_shared(p); }
__device__ __forceinline__ uint64_t make_desc(uint32_t addr, uint32_t lbo, uint32_t sbo, uint32_t swz = 0) {
    uint64_t d = 0;
    d |= (uint64_t)((addr & 0x3FFFF) >> 4);
    d |= (uint64_t)((lbo >> 4) & 0x3FFF) << 16;
    d |= (uint64_t)((sbo >> 4) & 0x3FFF) << 32;
    d |= (uint64_t)swz << 62;
    return d;
}
__device__ __forceinline__ void mbar_init(uint32_t bar, uint32_t count) {
    asm volatile("mbarrier.init.shared::cta.b64 [%0], %1;\n" ::"r"(bar), "r"(count) : "memory");
}
__device__ __forceinline__ void mbar_expect_tx(uint32_t bar, uint32_t bytes) {
    asm volatile("mbarrier.arrive.expect_tx.shared::cta.b64 _, [%0], %1;\n" ::"r"(bar), "r"(bytes) : "memory");
}
__device__ __forceinline__ void mbar_wait(uint32_t bar, uint32_t parity) {
    asm volatile(
        "{\n.reg .pred p;\n"
        "WAIT_LOOP:\n"
        "mbarrier.try_wait.parity.shared::cta.b64 p, [%0], %1;\n"
        "@p bra WAIT_DONE;\n"
        "bra WAIT_LOOP;\n"
        "WAIT_DONE:\n}\n" ::"r"(bar), "r"(parity) : "memory");
}
__device__ __forceinline__ void tma_load_2d(uint32_t dst, const CUtensorMap* tm, uint32_t bar, int c0, int c1) {
    asm volatile(
        "cp.async.bulk.tensor.2d.shared::cluster.global.mbarrier::complete_tx::bytes [%0], [%1, {%3, %4}], [%2];\n" ::"r"(dst),
        "l"(reinterpret_cast<uint64_t>(tm)), "r"(bar), "r"(c0), "r"(c1)
        : "memory");
}
__device__ __forceinline__ void wg_fence() { asm volatile("wgmma.fence.sync.aligned;\n" ::: "memory"); }
__device__ __forceinline__ void wg_commit() { asm volatile("wgmma.commit_group.sync.aligned;\n" ::: "memory"); }
template <int N>
__device__ __forceinline__ void wg_wait() { asm volatile("wgmma.wait_group.sync.aligned %0;\n" ::"n"(N) : "memory"); }
__device__ __forceinline__ void wg_bar(int id) { asm volatile("bar.sync %0, 128;" ::"r"(id) : "memory"); }
__device__ __forceinline__ void proxy_fence() {
 asm volatile("fence.proxy.async.shared::cta;\n" ::: "memory"); }
__device__ __forceinline__ void cp_async16(uint32_t dst, const void* src) {
    asm volatile("cp.async.cg.shared.global [%0], [%1], 16;\n" ::"r"(dst), "l"(src) : "memory");
}
__device__ __forceinline__ void cp_async_commit() { asm volatile("cp.async.commit_group;\n" ::: "memory"); }
__device__ __forceinline__ void cp_async_wait_all() { asm volatile("cp.async.wait_group 0;\n" ::: "memory"); }
__device__ __forceinline__ void prefetch_l2(const void* p) { asm volatile("prefetch.global.L2 [%0];\n" ::"l"(p)); }

__device__ __forceinline__ float tanh_approx(float x) {
    float y;
    asm("tanh.approx.f32 %0, %1;" : "=f"(y) : "f"(x));
    return y;
}
__device__ __forceinline__ uint32_t pack_bf16(float lo, float hi) {
    uint32_t r;
    asm("cvt.rn.bf16x2.f32 %0, %1, %2;" : "=r"(r) : "f"(hi), "f"(lo));
    return r;
}
__device__ __forceinline__ float bf_lo(uint32_t v) { return __uint_as_float(v << 16); }
__device__ __forceinline__ float bf_hi(uint32_t v) { return __uint_as_float(v & 0xffff0000u); }

#define ACC32(d)                                                                                             \
    "+f"(d[0]), "+f"(d[1]), "+f"(d[2]), "+f"(d[3]), "+f"(d[4]), "+f"(d[5]), "+f"(d[6]), "+f"(d[7]),          \
        "+f"(d[8]), "+f"(d[9]), "+f"(d[10]), "+f"(d[11]), "+f"(d[12]), "+f"(d[13]), "+f"(d[14]), "+f"(d[15]), \
        "+f"(d[16]), "+f"(d[17]), "+f"(d[18]), "+f"(d[19]), "+f"(d[20]), "+f"(d[21]), "+f"(d[22]),           \
        "+f"(d[23]), "+f"(d[24]), "+f"(d[25]), "+f"(d[26]), "+f"(d[27]), "+f"(d[28]), "+f"(d[29]),           \
        "+f"(d[30]), "+f"(d[31])
#define ACC32_STR                                                                \
    "{%0, %1, %2, %3, %4, %5, %6, %7, %8, %9, %10, %11, %12, %13, %14, %15, "    \
    " %16, %17, %18, %19, %20, %21, %22, %23, %24, %25, %26, %27, %28, %29, %30, %31}"

__device__ __forceinline__ void wgmma_ss_n64_tA(float (&d)[32], uint64_t adesc, uint64_t bdesc, int scale_d) {
    asm volatile(
        "{\n.reg .pred p;\nsetp.ne.b32 p, %34, 0;\n"
        "wgmma.mma_async.sync.aligned.m64n64k16.f32.bf16.bf16 " ACC32_STR ", %32, %33, p, 1, 1, 1, 0;\n}\n"
        : ACC32(d)
        : "l"(adesc), "l"(bdesc), "r"(scale_d));
}
__device__ __forceinline__ void wgmma_ss_n64(float (&d)[32], uint64_t adesc, uint64_t bdesc, int scale_d) {
    asm volatile(
        "{\n.reg .pred p;\nsetp.ne.b32 p, %34, 0;\n"
        "wgmma.mma_async.sync.aligned.m64n64k16.f32.bf16.bf16 " ACC32_STR ", %32, %33, p, 1, 1, 0, 1;\n}\n"
        : ACC32(d)
        : "l"(adesc), "l"(bdesc), "r"(scale_d));
}
__device__ __forceinline__ void wgmma_n96(float (&d)[48], uint32_t a0, uint32_t a1, uint32_t a2, uint32_t a3,
                                          uint64_t bdesc) {
    asm volatile(
        "{\n"
        "wgmma.mma_async.sync.aligned.m64n96k16.f32.bf16.bf16 "
        "{%0, %1, %2, %3, %4, %5, %6, %7, %8, %9, %10, %11, %12, %13, %14, %15, "
        " %16, %17, %18, %19, %20, %21, %22, %23, %24, %25, %26, %27, %28, %29, %30, %31, "
        " %32, %33, %34, %35, %36, %37, %38, %39, %40, %41, %42, %43, %44, %45, %46, %47}, "
        "{%48, %49, %50, %51}, %52, 1, 1, 1, 1;\n"
        "}\n"
        : ACC32(d), "+f"(d[32]), "+f"(d[33]), "+f"(d[34]), "+f"(d[35]), "+f"(d[36]), "+f"(d[37]), "+f"(d[38]),
          "+f"(d[39]), "+f"(d[40]), "+f"(d[41]), "+f"(d[42]), "+f"(d[43]), "+f"(d[44]), "+f"(d[45]), "+f"(d[46]),
          "+f"(d[47])
        : "r"(a0), "r"(a1), "r"(a2), "r"(a3), "l"(bdesc));
}

#define W2_LBO 128
#define W2_SBO (48 * 128)
#define W1_BOX_BYTES (96 * 128)
#define Y_BOX_BYTES (64 * 64)
#define Y_TILE_BYTES (3 * Y_BOX_BYTES)

__device__ __forceinline__ void ln_row4(const uint4 (&xv)[3], const float* __restrict__ s_dwq, uint4 (&y)[3]) {
    float xf[24], dwf[24];
    float s = 0.f;
#pragma unroll
    for (int i = 0; i < 3; i++) {
        uint32_t w[4] = {xv[i].x, xv[i].y, xv[i].z, xv[i].w};
        float4 da = *reinterpret_cast<const float4*>(s_dwq + 32 * i);
        float4 db = *reinterpret_cast<const float4*>(s_dwq + 32 * i + 4);
        dwf[i * 8 + 0] = da.x; dwf[i * 8 + 1] = da.y; dwf[i * 8 + 2] = da.z; dwf[i * 8 + 3] = da.w;
        dwf[i * 8 + 4] = db.x; dwf[i * 8 + 5] = db.y; dwf[i * 8 + 6] = db.z; dwf[i * 8 + 7] = db.w;
#pragma unroll
        for (int p = 0; p < 4; p++) {
            xf[i * 8 + 2 * p] = bf_lo(w[p]);
            xf[i * 8 + 2 * p + 1] = bf_hi(w[p]);
        }
#pragma unroll
        for (int p = 0; p < 8; p++) s = fmaf(xf[i * 8 + p], dwf[i * 8 + p], s);
    }
    s += __shfl_xor_sync(0xffffffffu, s, 1);
    s += __shfl_xor_sync(0xffffffffu, s, 2);
    float nmean = s * (-1.0f / C_IN);
    float v = 0.f;
#pragma unroll
    for (int i = 0; i < 24; i++) {
        xf[i] = fmaf(xf[i], dwf[i], nmean);
        v = fmaf(xf[i], xf[i], v);
    }
    v += __shfl_xor_sync(0xffffffffu, v, 1);
    v += __shfl_xor_sync(0xffffffffu, v, 2);
    float rstd = rsqrtf(v * (1.0f / C_IN) + 1e-5f) * GELU_KAPPA;
#pragma unroll
    for (int i = 0; i < 3; i++) {
        y[i].x = pack_bf16(xf[i * 8 + 0] * rstd, xf[i * 8 + 1] * rstd);
        y[i].y = pack_bf16(xf[i * 8 + 2] * rstd, xf[i * 8 + 3] * rstd);
        y[i].z = pack_bf16(xf[i * 8 + 4] * rstd, xf[i * 8 + 5] * rstd);
        y[i].w = pack_bf16(xf[i * 8 + 6] * rstd, xf[i * 8 + 7] * rstd);
    }
}

__device__ __forceinline__ void ln_tile_inplace(unsigned char* yp, const float* __restrict__ s_dwq) {
    uint4 xv[3], y[3];
#pragma unroll
    for (int i = 0; i < 3; i++) xv[i] = *reinterpret_cast<const uint4*>(yp + i * Y_BOX_BYTES);
    ln_row4(xv, s_dwq, y);
#pragma unroll
    for (int i = 0; i < 3; i++) *reinterpret_cast<uint4*>(yp + i * Y_BOX_BYTES) = y[i];
#pragma unroll
    for (int i = 0; i < 3; i++) xv[i] = *reinterpret_cast<const uint4*>(yp + 512 + i * Y_BOX_BYTES);
    ln_row4(xv, s_dwq, y);
#pragma unroll
    for (int i = 0; i < 3; i++) *reinterpret_cast<uint4*>(yp + 512 + i * Y_BOX_BYTES) = y[i];
}

__device__ __forceinline__ float gelu2(float u) {
    float t = fmaf(u, u, GELU_C0K);
    float a = t * u;
    float th = tanh_approx(a);
    return fmaf(u, th, u);
}

__device__ __forceinline__ void tma_x_tile(uint32_t dst, const CUtensorMap* tmx, uint32_t bar, int tile) {
    mbar_expect_tx(bar, Y_TILE_BYTES);
#pragma unroll
    for (int i = 0; i < 3; i++) tma_load_2d(dst + i * Y_BOX_BYTES, tmx, bar, i * 32, tile * TILE_M);
}

__global__ void __launch_bounds__(NTHR, 1)
k_stats(const __grid_constant__ CUtensorMap tm_x, const __grid_constant__ CUtensorMap tm_w1,
        const __nv_bfloat16* __restrict__ dw, const __nv_bfloat16* __restrict__ w2,
        const __nv_bfloat16* __restrict__ grn_g, const __nv_bfloat16* __restrict__ grn_b) {
    extern __shared__ __align__(1024) unsigned char smem[];
    unsigned char* s_w1 = smem;
    unsigned char* s_y = smem + 73728;
    float* s_dw = reinterpret_cast<float*>(smem + 73728 + NWG * 2 * Y_TILE_BYTES);
    float* s_red = s_dw + 128;
    uint64_t* s_bar = reinterpret_cast<uint64_t*>(s_red + C_H);

    const int tid = threadIdx.x;
    const int wg = tid >> 7;
    const int warp = (tid >> 5) & 3;
    const int lane = tid & 31;
    const int q = lane & 3;
    const int nwg = gridDim.x * NWG;
    int tile = blockIdx.x * NWG + wg;

    if (tid == 0) {
        for (int i = 0; i < 1 + 2 * NWG; i++) mbar_init(smem_u32(s_bar + i), 1);
        asm volatile("fence.mbarrier_init.release.cluster;\n" ::: "memory");
    }
    __shared__ float s_gb[2 * C_H];
    if (tid < C_IN) s_dw[tid] = __bfloat162float(dw[tid]);
    if (tid < C_H) { s_gb[tid] = __bfloat162float(grn_g[tid]); s_gb[C_H + tid] = __bfloat162float(grn_b[tid]); }
    for (int i = tid; i < C_H; i += NTHR) s_red[i] = 0.f;
    __syncthreads();
    const uint32_t ybuf0 = smem_u32(s_y + wg * 2 * Y_TILE_BYTES);
    const uint32_t bar_y = smem_u32(s_bar + 1 + 2 * wg);
    if (tid == 0) {
        mbar_expect_tx(smem_u32(s_bar), 6 * W1_BOX_BYTES);
        for (int i = 0; i < 6; i++) tma_load_2d(smem_u32(s_w1) + i * W1_BOX_BYTES, &tm_w1, smem_u32(s_bar), i * 64, 0);
    }
    if ((tid & 127) == 0 && tile < NTILES) tma_x_tile(ybuf0, &tm_x, bar_y, tile);

    asm volatile("griddepcontrol.launch_dependents;\n" ::: "memory");
    if (blockIdx.x == 0) {
        prefetch_l2(reinterpret_cast<const unsigned char*>(w2) + tid * 128);
        if (tid < 64) prefetch_l2(reinterpret_cast<const unsigned char*>(w2) + (512 + tid) * 128);
    }
    float ss[12];
#pragma unroll
    for (int i = 0; i < 12; i++) ss[i] = 0.f;

    const uint64_t w1_desc = make_desc(smem_u32(s_w1), W1_BOX_BYTES, 1024, 1);
    const int rl = warp * 16 + (lane >> 2);
    const int yoff = rl * 64 + ((q ^ ((rl >> 1) & 3)) * 16);
    mbar_wait(smem_u32(s_bar), 0);

    int it = 0;
    for (; tile < NTILES; tile += nwg, it++) {
        const int buf = it & 1;
        if ((tid & 127) == 0 && tile + nwg < NTILES) tma_x_tile(ybuf0 + (buf ^ 1) * Y_TILE_BYTES, &tm_x, bar_y + (buf ^ 1) * 8, tile + nwg);
        mbar_wait(bar_y + buf * 8, (it >> 1) & 1);
        unsigned char* ytile = s_y + (wg * 2 + buf) * Y_TILE_BYTES;
        ln_tile_inplace(ytile + yoff, s_dw + 8 * q);
        proxy_fence();
        wg_bar(1 + wg);
        const uint64_t y_desc = make_desc(smem_u32(ytile), 16, 512, 2);
        float S[2][32];
        wg_fence();
#pragma unroll
        for (int t = 0; t < 6; t++)
            wgmma_ss_n64_tA(S[0], w1_desc + ((t * 2048) >> 4), y_desc + (((t >> 1) * Y_BOX_BYTES + (t & 1) * 32) >> 4), t != 0);
        wg_commit();
#pragma unroll
        for (int m = 0; m < 6; m++) {
            if (m + 1 < 6) {
                wg_fence();
#pragma unroll
                for (int t = 0; t < 6; t++)
                    wgmma_ss_n64_tA(S[(m + 1) & 1], w1_desc + (((m + 1) * W1_BOX_BYTES + t * 2048) >> 4),
                                    y_desc + (((t >> 1) * Y_BOX_BYTES + (t & 1) * 32) >> 4), t != 0);
                wg_commit();
                wg_wait<1>();
            } else {
                wg_wait<0>();
            }
            float(&Sc)[32] = S[m & 1];
            float a0 = ss[2 * m], a1 = ss[2 * m + 1];
#pragma unroll
            for (int j = 0; j < 8; j++) {
                float g0 = gelu2(Sc[4 * j]);
                float g1 = gelu2(Sc[4 * j + 1]);
                float g2 = gelu2(Sc[4 * j + 2]);
                float g3 = gelu2(Sc[4 * j + 3]);
                a0 = fmaf(g0, g0, a0);
                a1 = fmaf(g2, g2, a1);
                a0 = fmaf(g1, g1, a0);
                a1 = fmaf(g3, g3, a1);
            }
            ss[2 * m] = a0;
            ss[2 * m + 1] = a1;
        }
        wg_bar(1 + wg);
    }
#pragma unroll
    for (int i = 0; i < 12; i++) {
        float v = ss[i];
        v += __shfl_xor_sync(0xffffffffu, v, 1);
        v += __shfl_xor_sync(0xffffffffu, v, 2);
        if (q == 0) {
            int m = i >> 1, hh = i & 1;
            atomicAdd(&s_red[m * 64 + warp * 16 + hh * 8 + (lane >> 2)], v);
        }
    }
    __syncthreads();
    const float sc = 0.25f / (GELU_KAPPA * GELU_KAPPA);
    for (int i = tid; i < C_H; i += NTHR) atomicAdd(&g_sum[i], s_red[i] * sc);
    __threadfence();
    __syncthreads();
    __shared__ unsigned int s_last;
    if (tid == 0) s_last = (atomicAdd(&g_done, 1u) == gridDim.x - 1);
    __syncthreads();
    if (!s_last) return;
    __threadfence();
    uint4 w2v[384 * 12 / NTHR];
#pragma unroll
    for (int i = 0; i < 384 * 12 / NTHR; i++) {
        int it2 = tid + i * NTHR;
        int kr = it2 & 7;
        int nb = (it2 >> 3) % 12;
        int kb = (it2 >> 3) / 12;
        w2v[i] = __ldg(reinterpret_cast<const uint4*>(w2 + (kb * 8 + kr) * C_IN + nb * 8));
    }
    float* s_s = s_red;
    float* s_tmp = s_dw;
    float lsum = 0.f;
    if (tid < C_H) {
        float gx = sqrtf(__ldcg(&g_sum[tid]) + 1e-6f);
        g_sum[tid] = 0.f;
        s_s[tid] = gx;
        lsum = gx;
    }
#pragma unroll
    for (int o = 16; o > 0; o >>= 1) lsum += __shfl_xor_sync(0xffffffffu, lsum, o);
    if (lane == 0) s_tmp[tid >> 5] = lsum;
    if (tid == 0) g_done = 0;
    __syncthreads();
    float tot = 0.f;
#pragma unroll
    for (int i = 0; i < NTHR / 32; i++) tot += s_tmp[i];
    float inv = 1.0f / (tot * (1.0f / C_H) + 1e-6f);
    __syncthreads();
    if (tid < C_H) s_s[tid] = (0.5f / GELU_KAPPA) * (1.0f + s_gb[tid] * (s_s[tid] * inv));
    if (tid < C_IN) s_tmp[tid] = 0.f;
    __syncthreads();
    {
        float a0 = 0.f, a1 = 0.f, a2 = 0.f;
        int kbase = (tid >> 5) * (C_H / (NTHR / 32));
#pragma unroll
        for (int k = kbase; k < kbase + C_H / (NTHR / 32); k++) {
            float b = s_gb[C_H + k];
            a0 = fmaf(b, __bfloat162float(w2[k * C_IN + lane]), a0);
            a1 = fmaf(b, __bfloat162float(w2[k * C_IN + lane + 32]), a1);
            a2 = fmaf(b, __bfloat162float(w2[k * C_IN + lane + 64]), a2);
        }
        atomicAdd(&s_tmp[lane], a0);
        atomicAdd(&s_tmp[lane + 32], a1);
        atomicAdd(&s_tmp[lane + 64], a2);
    }
#pragma unroll
    for (int i = 0; i < 384 * 12 / NTHR; i++) {
        int it2 = tid + i * NTHR;
        int kr = it2 & 7;
        int nb = (it2 >> 3) % 12;
        int kb = (it2 >> 3) / 12;
        float sk = s_s[kb * 8 + kr];
        uint4 v = w2v[i];
        uint4 o;
        o.x = pack_bf16(sk * bf_lo(v.x), sk * bf_hi(v.x));
        o.y = pack_bf16(sk * bf_lo(v.y), sk * bf_hi(v.y));
        o.z = pack_bf16(sk * bf_lo(v.z), sk * bf_hi(v.z));
        o.w = pack_bf16(sk * bf_lo(v.w), sk * bf_hi(v.w));
        *reinterpret_cast<uint4*>(g_w2img + nb * W2_SBO + kb * W2_LBO + kr * 16) = o;
    }
    __syncthreads();
    if (tid < C_IN) g_c[tid] = s_tmp[tid];
}

#define NWG2 3
#define NTHR2 (NWG2 * 128)

__device__ __forceinline__ void wgmma_rs_n64(float (&d)[32], uint32_t a0, uint32_t a1, uint32_t a2, uint32_t a3,
                                             uint64_t bdesc, int scale_d) {
    asm volatile(
        "{\n.reg .pred p;\nsetp.ne.b32 p, %37, 0;\n"
        "wgmma.mma_async.sync.aligned.m64n64k16.f32.bf16.bf16 " ACC32_STR ", {%32, %33, %34, %35}, %36, p, 1, 1, 1;\n}\n"
        : ACC32(d)
        : "r"(a0), "r"(a1), "r"(a2), "r"(a3), "l"(bdesc), "r"(scale_d));
}
__device__ __forceinline__ void ldsm_x4(uint32_t addr, uint32_t& r0, uint32_t& r1, uint32_t& r2, uint32_t& r3) {
    asm volatile("ldmatrix.sync.aligned.m8n8.x4.shared.b16 {%0, %1, %2, %3}, [%4];\n"
                 : "=r"(r0), "=r"(r1), "=r"(r2), "=r"(r3) : "r"(addr) : "memory");
}
__device__ __forceinline__ void stsm_x4(uint32_t addr, uint32_t r0, uint32_t r1, uint32_t r2, uint32_t r3) {
    asm volatile("stmatrix.sync.aligned.m8n8.x4.shared.b16 [%0], {%1, %2, %3, %4};\n" ::"r"(addr), "r"(r0), "r"(r1), "r"(r2),
                 "r"(r3) : "memory");
}
__device__ __forceinline__ void tma_store_2d(const CUtensorMap* tm, uint32_t src, int c0, int c1) {
    asm volatile("cp.async.bulk.tensor.2d.global.shared::cta.bulk_group [%0, {%2, %3}], [%1];\n" ::"l"(
                     reinterpret_cast<uint64_t>(tm)), "r"(src), "r"(c0), "r"(c1) : "memory");
}

__device__ __forceinline__ void ln_frag(uint32_t (&f)[6][4], const float* __restrict__ s_dwq) {
    float xa[24], xb[24], dwf[24];
    float sa = 0.f, sb = 0.f;
#pragma unroll
    for (int t = 0; t < 6; t++) {
#pragma unroll
        for (int h = 0; h < 2; h++) {
            float2 d = *reinterpret_cast<const float2*>(s_dwq + 16 * t + 8 * h);
            int i = t * 4 + h * 2;
            dwf[i] = d.x; dwf[i + 1] = d.y;
            xa[i] = bf_lo(f[t][2 * h]); xa[i + 1] = bf_hi(f[t][2 * h]);
            xb[i] = bf_lo(f[t][2 * h + 1]); xb[i + 1] = bf_hi(f[t][2 * h + 1]);
            sa = fmaf(xa[i], d.x, sa); sa = fmaf(xa[i + 1], d.y, sa);
            sb = fmaf(xb[i], d.x, sb); sb = fmaf(xb[i + 1], d.y, sb);
        }
    }
    sa += __shfl_xor_sync(0xffffffffu, sa, 1);
    sb += __shfl_xor_sync(0xffffffffu, sb, 1);
    sa += __shfl_xor_sync(0xffffffffu, sa, 2);
    sb += __shfl_xor_sync(0xffffffffu, sb, 2);
    float ma = sa * (-1.0f / C_IN), mb = sb * (-1.0f / C_IN);
    float va = 0.f, vb = 0.f;
#pragma unroll
    for (int i = 0; i < 24; i++) {
        xa[i] = fmaf(xa[i], dwf[i], ma);
        xb[i] = fmaf(xb[i], dwf[i], mb);
        va = fmaf(xa[i], xa[i], va);
        vb = fmaf(xb[i], xb[i], vb);
    }
    va += __shfl_xor_sync(0xffffffffu, va, 1);
    vb += __shfl_xor_sync(0xffffffffu, vb, 1);
    va += __shfl_xor_sync(0xffffffffu, va, 2);
    vb += __shfl_xor_sync(0xffffffffu, vb, 2);
    float ra = rsqrtf(va * (1.0f / C_IN) + 1e-5f) * GELU_KAPPA;
    float rb = rsqrtf(vb * (1.0f / C_IN) + 1e-5f) * GELU_KAPPA;
#pragma unroll
    for (int t = 0; t < 6; t++) {
#pragma unroll
        for (int h = 0; h < 2; h++) {
            int i = t * 4 + h * 2;
            f[t][2 * h] = pack_bf16(xa[i] * ra, xa[i + 1] * ra);
            f[t][2 * h + 1] = pack_bf16(xb[i] * rb, xb[i + 1] * rb);
        }
    }
}

__global__ void __launch_bounds__(NTHR2, 1)
k_main(const __grid_constant__ CUtensorMap tm_x, const __grid_constant__ CUtensorMap tm_w1,
       const __grid_constant__ CUtensorMap tm_out, const __nv_bfloat16* __restrict__ dw) {
    extern __shared__ __align__(1024) unsigned char smem[];
    unsigned char* s_w1 = smem;
    unsigned char* s_w2 = smem + 73728;
    unsigned char* s_x = smem + 2 * 73728;
    float* s_dw = reinterpret_cast<float*>(smem + 2 * 73728 + NWG2 * 2 * Y_TILE_BYTES);
    float* s_c = s_dw + 128;
    uint64_t* s_bar = reinterpret_cast<uint64_t*>(s_c + 128);

    const int tid = threadIdx.x;
    const int wg = tid >> 7;
    const int warp = (tid >> 5) & 3;
    const int lane = tid & 31;
    const int q = lane & 3;
    const int nwg = gridDim.x * NWG2;
    int tile = blockIdx.x * NWG2 + wg;

    const uint32_t xbuf0 = smem_u32(s_x + wg * 2 * Y_TILE_BYTES);
    const uint32_t bar_x = smem_u32(s_bar + 1 + 2 * wg);
    if (tid == 0) {
        for (int i = 0; i < 1 + 2 * NWG2; i++) mbar_init(smem_u32(s_bar + i), 1);
        asm volatile("fence.mbarrier_init.release.cluster;\n" ::: "memory");
    }
    if (tid < C_IN) s_dw[tid] = __bfloat162float(dw[tid]);
    __syncthreads();
    if ((tid & 127) == 0 && tile < NTILES) tma_x_tile(xbuf0, &tm_x, bar_x, tile);
    if (tid == 0) {
        mbar_expect_tx(smem_u32(s_bar), 6 * W1_BOX_BYTES + 73728);
        for (int i = 0; i < 6; i++) tma_load_2d(smem_u32(s_w1) + i * W1_BOX_BYTES, &tm_w1, smem_u32(s_bar), i * 64, 0);
    }
    asm volatile("griddepcontrol.wait;\n" ::: "memory");
    if (tid < C_IN) s_c[tid] = __ldcg(&g_c[tid]);
    if (tid == 0) {
        for (int i = 0; i < 6; i++)
            asm volatile("cp.async.bulk.shared::cluster.global.mbarrier::complete_tx::bytes [%0], [%1], %2, [%3];\n" ::"r"(
                             smem_u32(s_w2) + i * 12288),
                         "l"(g_w2img + i * 12288), "r"(12288), "r"(smem_u32(s_bar))
                         : "memory");
    }
    __syncthreads();
    mbar_wait(smem_u32(s_bar), 0);

    const uint64_t w1_desc = make_desc(smem_u32(s_w1), W1_BOX_BYTES, 1024, 1);
    const uint64_t w2_desc = make_desc(smem_u32(s_w2), W2_LBO, W2_SBO, 0);
    const int lrow = warp * 16 + ((lane >> 3) & 1) * 8 + (lane & 7);
    const int lhalf = lane >> 4;
    const int lsw = (lrow >> 1) & 3;
    const uint32_t loff0 = lrow * 64 + (((0 + lhalf) ^ lsw) << 4);
    const uint32_t loff1 = lrow * 64 + (((2 + lhalf) ^ lsw) << 4);

    int it = 0;
    for (; tile < NTILES; tile += nwg, it++) {
        const int buf = it & 1;
        const uint32_t xb = xbuf0 + buf * Y_TILE_BYTES;
        if ((tid & 127) == 0 && tile + nwg < NTILES) {
            asm volatile("cp.async.bulk.wait_group.read 0;\n" ::: "memory");
            tma_x_tile(xbuf0 + (buf ^ 1) * Y_TILE_BYTES, &tm_x, bar_x + (buf ^ 1) * 8, tile + nwg);
        }
        mbar_wait(bar_x + buf * 8, (it >> 1) & 1);
        uint32_t f[6][4];
#pragma unroll
        for (int t = 0; t < 6; t++)
            ldsm_x4(xb + (t >> 1) * Y_BOX_BYTES + ((t & 1) ? loff1 : loff0), f[t][0], f[t][1], f[t][2], f[t][3]);
        ln_frag(f, s_dw + 2 * q);

        float O[48];
#pragma unroll
        for (int j = 0; j < 12; j++) {
            float2 cc = *reinterpret_cast<const float2*>(&s_c[8 * j + 2 * q]);
            O[4 * j] = cc.x; O[4 * j + 1] = cc.y; O[4 * j + 2] = cc.x; O[4 * j + 3] = cc.y;
        }
        float S[32];
        uint32_t hf[16];
        wg_fence();
#pragma unroll
        for (int t = 0; t < 6; t++) wgmma_rs_n64(S, f[t][0], f[t][1], f[t][2], f[t][3], w1_desc + ((t * 2048) >> 4), t != 0);
        wg_commit();
#pragma unroll
        for (int c = 0; c < 6; c++) {
            wg_wait<0>();
#pragma unroll
            for (int j = 0; j < 8; j++) {
                float g0 = gelu2(S[4 * j]);
                float g1 = gelu2(S[4 * j + 1]);
                float g2 = gelu2(S[4 * j + 2]);
                float g3 = gelu2(S[4 * j + 3]);
                hf[2 * j] = pack_bf16(g0, g1);
                hf[2 * j + 1] = pack_bf16(g2, g3);
            }
            wg_fence();
#pragma unroll
            for (int t = 0; t < 4; t++)
                wgmma_n96(O, hf[4 * t], hf[4 * t + 1], hf[4 * t + 2], hf[4 * t + 3],
                          w2_desc + (((c * 8 + 2 * t) * W2_LBO) >> 4));
            if (c + 1 < 6) {
#pragma unroll
                for (int t = 0; t < 6; t++)
                    wgmma_rs_n64(S, f[t][0], f[t][1], f[t][2], f[t][3],
                                 w1_desc + (((c + 1) * W1_BOX_BYTES + t * 2048) >> 4), t != 0);
            }
            wg_commit();
        }
        uint32_t xr[6][4];
#pragma unroll
        for (int t = 0; t < 6; t++)
            ldsm_x4(xb + (t >> 1) * Y_BOX_BYTES + ((t & 1) ? loff1 : loff0), xr[t][0], xr[t][1], xr[t][2], xr[t][3]);
        wg_wait<0>();
#pragma unroll
        for (int t = 0; t < 6; t++) {
            uint32_t o0 = pack_bf16(bf_lo(xr[t][0]) + O[8 * t + 0], bf_hi(xr[t][0]) + O[8 * t + 1]);
            uint32_t o1 = pack_bf16(bf_lo(xr[t][1]) + O[8 * t + 2], bf_hi(xr[t][1]) + O[8 * t + 3]);
            uint32_t o2 = pack_bf16(bf_lo(xr[t][2]) + O[8 * t + 4], bf_hi(xr[t][2]) + O[8 * t + 5]);
            uint32_t o3 = pack_bf16(bf_lo(xr[t][3]) + O[8 * t + 6], bf_hi(xr[t][3]) + O[8 * t + 7]);
            stsm_x4(xb + (t >> 1) * Y_BOX_BYTES + ((t & 1) ? loff1 : loff0), o0, o1, o2, o3);
        }
        proxy_fence();
        wg_bar(1 + wg);
        if ((tid & 127) == 0) {
#pragma unroll
            for (int i = 0; i < 3; i++) tma_store_2d(&tm_out, xb + i * Y_BOX_BYTES, i * 32, tile * TILE_M);
            asm volatile("cp.async.bulk.commit_group;\n" ::: "memory");
        }
    }
    if ((tid & 127) == 0) asm volatile("cp.async.bulk.wait_group 0;\n" ::: "memory");
}

#define SMEM1 (73728 + NWG * 2 * Y_TILE_BYTES + 512 + 1536 + 128)
#define SMEM2 (2 * 73728 + NWG2 * 2 * Y_TILE_BYTES + 512 + 512 + 64)

typedef CUresult (*PFN_encodeTiled)(CUtensorMap*, CUtensorMapDataType, cuuint32_t, void*, const cuuint64_t*, const cuuint64_t*,
                                    const cuuint32_t*, const cuuint32_t*, CUtensorMapInterleave, CUtensorMapSwizzle,
                                    CUtensorMapL2promotion, CUtensorMapFloatOOBfill);

extern "C" void kernel_launch(void* const* d_in, const int* in_sizes, int n_in, void* d_out, int out_size) {
    const __nv_bfloat16* x = (const __nv_bfloat16*)d_in[0];
    const __nv_bfloat16* dw = (const __nv_bfloat16*)d_in[1];
    const __nv_bfloat16* w1 = (const __nv_bfloat16*)d_in[2];
    const __nv_bfloat16* w2 = (const __nv_bfloat16*)d_in[3];
    const __nv_bfloat16* grn_g = (const __nv_bfloat16*)d_in[4];
    const __nv_bfloat16* grn_b = (const __nv_bfloat16*)d_in[5];

    static int n_sm = 0;
    static CUtensorMap tm_x, tm_w1, tm_out;
    static const void* last_x = nullptr;
    static const void* last_w1 = nullptr;
    static const void* last_out = nullptr;
    static PFN_encodeTiled encode = nullptr;
    if (n_sm == 0) {
        int dev = 0;
        cudaGetDevice(&dev);
        cudaDeviceGetAttribute(&n_sm, cudaDevAttrMultiProcessorCount, dev);
        if (n_sm > MAX_CTAS) n_sm = MAX_CTAS;
        cudaFuncSetAttribute(k_stats, cudaFuncAttributeMaxDynamicSharedMemorySize, SMEM1);
        cudaFuncSetAttribute(k_main, cudaFuncAttributeMaxDynamicSharedMemorySize, SMEM2);
        cudaDriverEntryPointQueryResult qres;
        void* fn = nullptr;
        cudaGetDriverEntryPoint("cuTensorMapEncodeTiled", &fn, cudaEnableDefault, &qres);
        encode = (PFN_encodeTiled)fn;
    }
    if (last_x != x || last_w1 != w1 || last_out != d_out) {
        cuuint64_t dims[2] = {96, (cuuint64_t)NROWS};
        cuuint64_t strides[1] = {192};
        cuuint32_t box[2] = {32, 64};
        cuuint32_t es[2] = {1, 1};
        encode(&tm_x, CU_TENSOR_MAP_DATA_TYPE_BFLOAT16, 2, (void*)x, dims, strides, box, es, CU_TENSOR_MAP_INTERLEAVE_NONE,
               CU_TENSOR_MAP_SWIZZLE_64B, CU_TENSOR_MAP_L2_PROMOTION_L2_128B, CU_TENSOR_MAP_FLOAT_OOB_FILL_NONE);
        encode(&tm_out, CU_TENSOR_MAP_DATA_TYPE_BFLOAT16, 2, d_out, dims, strides, box, es, CU_TENSOR_MAP_INTERLEAVE_NONE,
               CU_TENSOR_MAP_SWIZZLE_64B, CU_TENSOR_MAP_L2_PROMOTION_L2_128B, CU_TENSOR_MAP_FLOAT_OOB_FILL_NONE);
        cuuint64_t dimsw[2] = {384, 96};
        cuuint64_t stridesw[1] = {768};
        cuuint32_t boxw[2] = {64, 96};
        encode(&tm_w1, CU_TENSOR_MAP_DATA_TYPE_BFLOAT16, 2, (void*)w1, dimsw, stridesw, boxw, es, CU_TENSOR_MAP_INTERLEAVE_NONE,
               CU_TENSOR_MAP_SWIZZLE_128B, CU_TENSOR_MAP_L2_PROMOTION_L2_128B, CU_TENSOR_MAP_FLOAT_OOB_FILL_NONE);
        last_x = x;
        last_w1 = w1;
        last_out = d_out;
    }
    k_stats<<<n_sm, NTHR, SMEM1>>>(tm_x, tm_w1, dw, w2, grn_g, grn_b);
    cudaLaunchConfig_t cfg = {};
    cfg.gridDim = dim3(n_sm);
    cfg.blockDim = dim3(NTHR2);
    cfg.dynamicSmemBytes = SMEM2;
    cfg.stream = cudaStreamPerThread;
    cudaLaunchAttribute attr[1];
    attr[0].id = cudaLaunchAttributeProgrammaticStreamSerialization;
    attr[0].val.programmaticStreamSerializationAllowed = 1;
    cfg.attrs = attr;
    cfg.numAttrs = 1;
    cudaLaunchKernelEx(&cfg, k_main, tm_x, tm_w1, tm_out, dw);
}
```

```cpp
#include <cuda_runtime.h>
#include <cuda_bf16.h>
#include <stdint.h>
#include <cuda.h>

#define C_IN 96
#define C_H 384
#define NROWS (512 * 512)
#define TILE_M 64
#define NTILES (NROWS / TILE_M)
#define MAX_CTAS 256
#define NWG 4
#define NTHR (NWG * 128)

#define TS(i)
#define TS0(i)
__device__ float g_sum[C_H];
__device__ unsigned int g_done;
__device__ __align__(1024) unsigned char g_w2img[73728];
__device__ float g_c[C_IN];
#define TSTAMP(i)

#define GELU_KAPPA 0.3292034911525734f
#define GELU_C0K 2.423681954311584f

__device__ __forceinline__ uint32_t smem_u32(const void* p) { return (uint32_t)__cvta_generic_to_shared(p); }
__device__ __forceinline__ uint64_t make_desc(uint32_t addr, uint32_t lbo, uint32_t sbo, uint32_t swz = 0) {
    uint64_t d = 0;
    d |= (uint64_t)((addr & 0x3FFFF) >> 4);
    d |= (uint64_t)((lbo >> 4) & 0x3FFF) << 16;
    d |= (uint64_t)((sbo >> 4) & 0x3FFF) << 32;
    d |= (uint64_t)swz << 62;
    return d;
}
__device__ __forceinline__ void mbar_init(uint32_t bar, uint32_t count) {
    asm volatile("mbarrier.init.shared::cta.b64 [%0], %1;\n" ::"r"(bar), "r"(count) : "memory");
}
__device__ __forceinline__ void mbar_expect_tx(uint32_t bar, uint32_t bytes) {
    asm volatile("mbarrier.arrive.expect_tx.shared::cta.b64 _, [%0], %1;\n" ::"r"(bar), "r"(bytes) : "memory");
}
__device__ __forceinline__ void mbar_wait(uint32_t bar, uint32_t parity) {
    asm volatile(
        "{\n.reg .pred p;\n"
        "WAIT_LOOP:\n"
        "mbarrier.try_wait.parity.shared::cta.b64 p, [%0], %1;\n"
        "@p bra WAIT_DONE;\n"
        "bra WAIT_LOOP;\n"
        "WAIT_DONE:\n}\n" ::"r"(bar), "r"(parity) : "memory");
}
__device__ __forceinline__ void tma_load_2d(uint32_t dst, const CUtensorMap* tm, uint32_t bar, int c0, int c1) {
    asm volatile(
        "cp.async.bulk.tensor.2d.shared::cluster.global.mbarrier::complete_tx::bytes [%0], [%1, {%3, %4}], [%2];\n" ::"r"(dst),
        "l"(reinterpret_cast<uint64_t>(tm)), "r"(bar), "r"(c0), "r"(c1)
        : "memory");
}
__device__ __forceinline__ void wg_fence() { asm volatile("wgmma.fence.sync.aligned;\n" ::: "memory"); }
__device__ __forceinline__ void wg_commit() { asm volatile("wgmma.commit_group.sync.aligned;\n" ::: "memory"); }
template <int N>
__device__ __forceinline__ void wg_wait() { asm volatile("wgmma.wait_group.sync.aligned %0;\n" ::"n"(N) : "memory"); }
__device__ __forceinline__ void wg_bar(int id) { asm volatile("bar.sync %0, 128;" ::"r"(id) : "memory"); }
__device__ __forceinline__ void proxy_fence() {
 asm volatile("fence.proxy.async.shared::cta;\n" ::: "memory"); }
__device__ __forceinline__ void cp_async16(uint32_t dst, const void* src) {
    asm volatile("cp.async.cg.shared.global [%0], [%1], 16;\n" ::"r"(dst), "l"(src) : "memory");
}
__device__ __forceinline__ void cp_async_commit() { asm volatile("cp.async.commit_group;\n" ::: "memory"); }
__device__ __forceinline__ void cp_async_wait_all() { asm volatile("cp.async.wait_group 0;\n" ::: "memory"); }
__device__ __forceinline__ void prefetch_l2(const void* p) { asm volatile("prefetch.global.L2 [%0];\n" ::"l"(p)); }

__device__ __forceinline__ float tanh_approx(float x) {
    float y;
    asm("tanh.approx.f32 %0, %1;" : "=f"(y) : "f"(x));
    return y;
}
__device__ __forceinline__ uint32_t pack_bf16(float lo, float hi) {
    uint32_t r;
    asm("cvt.rn.bf16x2.f32 %0, %1, %2;" : "=r"(r) : "f"(hi), "f"(lo));
    return r;
}
__device__ __forceinline__ float bf_lo(uint32_t v) { return __uint_as_float(v << 16); }
__device__ __forceinline__ float bf_hi(uint32_t v) { return __uint_as_float(v & 0xffff0000u); }

#define ACC32(d)                                                                                             \
    "+f"(d[0]), "+f"(d[1]), "+f"(d[2]), "+f"(d[3]), "+f"(d[4]), "+f"(d[5]), "+f"(d[6]), "+f"(d[7]),          \
        "+f"(d[8]), "+f"(d[9]), "+f"(d[10]), "+f"(d[11]), "+f"(d[12]), "+f"(d[13]), "+f"(d[14]), "+f"(d[15]), \
        "+f"(d[16]), "+f"(d[17]), "+f"(d[18]), "+f"(d[19]), "+f"(d[20]), "+f"(d[21]), "+f"(d[22]),           \
        "+f"(d[23]), "+f"(d[24]), "+f"(d[25]), "+f"(d[26]), "+f"(d[27]), "+f"(d[28]), "+f"(d[29]),           \
        "+f"(d[30]), "+f"(d[31])
#define ACC32_STR                                                                \
    "{%0, %1, %2, %3, %4, %5, %6, %7, %8, %9, %10, %11, %12, %13, %14, %15, "    \
    " %16, %17, %18, %19, %20, %21, %22, %23, %24, %25, %26, %27, %28, %29, %30, %31}"

__device__ __forceinline__ void wgmma_ss_n64_tA(float (&d)[32], uint64_t adesc, uint64_t bdesc, int scale_d) {
    asm volatile(
        "{\n.reg .pred p;\nsetp.ne.b32 p, %34, 0;\n"
        "wgmma.mma_async.sync.aligned.m64n64k16.f32.bf16.bf16 " ACC32_STR ", %32, %33, p, 1, 1, 1, 0;\n}\n"
        : ACC32(d)
        : "l"(adesc), "l"(bdesc), "r"(scale_d));
}
__device__ __forceinline__ void wgmma_ss_n64(float (&d)[32], uint64_t adesc, uint64_t bdesc, int scale_d) {
    asm volatile(
        "{\n.reg .pred p;\nsetp.ne.b32 p, %34, 0;\n"
        "wgmma.mma_async.sync.aligned.m64n64k16.f32.bf16.bf16 " ACC32_STR ", %32, %33, p, 1, 1, 0, 1;\n}\n"
        : ACC32(d)
        : "l"(adesc), "l"(bdesc), "r"(scale_d));
}
__device__ __forceinline__ void wgmma_n96(float (&d)[48], uint32_t a0, uint32_t a1, uint32_t a2, uint32_t a3,
                                          uint64_t bdesc) {
    asm volatile(
        "{\n"
        "wgmma.mma_async.sync.aligned.m64n96k16.f32.bf16.bf16 "
        "{%0, %1, %2, %3, %4, %5, %6, %7, %8, %9, %10, %11, %12, %13, %14, %15, "
        " %16, %17, %18, %19, %20, %21, %22, %23, %24, %25, %26, %27, %28, %29, %30, %31, "
        " %32, %33, %34, %35, %36, %37, %38, %39, %40, %41, %42, %43, %44, %45, %46, %47}, "
        "{%48, %49, %50, %51}, %52, 1, 1, 1, 1;\n"
        "}\n"
        : ACC32(d), "+f"(d[32]), "+f"(d[33]), "+f"(d[34]), "+f"(d[35]), "+f"(d[36]), "+f"(d[37]), "+f"(d[38]),
          "+f"(d[39]), "+f"(d[40]), "+f"(d[41]), "+f"(d[42]), "+f"(d[43]), "+f"(d[44]), "+f"(d[45]), "+f"(d[46]),
          "+f"(d[47])
        : "r"(a0), "r"(a1), "r"(a2), "r"(a3), "l"(bdesc));
}

#define W2_LBO 128
#define W2_SBO (48 * 128)
#define W1_BOX_BYTES (96 * 128)
#define Y_BOX_BYTES (64 * 64)
#define Y_TILE_BYTES (3 * Y_BOX_BYTES)

__device__ __forceinline__ void ln_row4(const uint4 (&xv)[3], const float* __restrict__ s_dwq, uint4 (&y)[3]) {
    float xf[24], dwf[24];
    float s = 0.f;
#pragma unroll
    for (int i = 0; i < 3; i++) {
        uint32_t w[4] = {xv[i].x, xv[i].y, xv[i].z, xv[i].w};
        float4 da = *reinterpret_cast<const float4*>(s_dwq + 32 * i);
        float4 db = *reinterpret_cast<const float4*>(s_dwq + 32 * i + 4);
        dwf[i * 8 + 0] = da.x; dwf[i * 8 + 1] = da.y; dwf[i * 8 + 2] = da.z; dwf[i * 8 + 3] = da.w;
        dwf[i * 8 + 4] = db.x; dwf[i * 8 + 5] = db.y; dwf[i * 8 + 6] = db.z; dwf[i * 8 + 7] = db.w;
#pragma unroll
        for (int p = 0; p < 4; p++) {
            xf[i * 8 + 2 * p] = bf_lo(w[p]);
            xf[i * 8 + 2 * p + 1] = bf_hi(w[p]);
        }
#pragma unroll
        for (int p = 0; p < 8; p++) s = fmaf(xf[i * 8 + p], dwf[i * 8 + p], s);
    }
    s += __shfl_xor_sync(0xffffffffu, s, 1);
    s += __shfl_xor_sync(0xffffffffu, s, 2);
    float nmean = s * (-1.0f / C_IN);
    float v = 0.f;
#pragma unroll
    for (int i = 0; i < 24; i++) {
        xf[i] = fmaf(xf[i], dwf[i], nmean);
        v = fmaf(xf[i], xf[i], v);
    }
    v += __shfl_xor_sync(0xffffffffu, v, 1);
    v += __shfl_xor_sync(0xffffffffu, v, 2);
    float rstd = rsqrtf(v * (1.0f / C_IN) + 1e-5f) * GELU_KAPPA;
#pragma unroll
    for (int i = 0; i < 3; i++) {
        y[i].x = pack_bf16(xf[i * 8 + 0] * rstd, xf[i * 8 + 1] * rstd);
        y[i].y = pack_bf16(xf[i * 8 + 2] * rstd, xf[i * 8 + 3] * rstd);
        y[i].z = pack_bf16(xf[i * 8 + 4] * rstd, xf[i * 8 + 5] * rstd);
        y[i].w = pack_bf16(xf[i * 8 + 6] * rstd, xf[i * 8 + 7] * rstd);
    }
}

__device__ __forceinline__ void ln_tile_inplace(unsigned char* yp, const float* __restrict__ s_dwq) {
    uint4 xv[3], y[3];
#pragma unroll
    for (int i = 0; i < 3; i++) xv[i] = *reinterpret_cast<const uint4*>(yp + i * Y_BOX_BYTES);
    ln_row4(xv, s_dwq, y);
#pragma unroll
    for (int i = 0; i < 3; i++) *reinterpret_cast<uint4*>(yp + i * Y_BOX_BYTES) = y[i];
#pragma unroll
    for (int i = 0; i < 3; i++) xv[i] = *reinterpret_cast<const uint4*>(yp + 512 + i * Y_BOX_BYTES);
    ln_row4(xv, s_dwq, y);
#pragma unroll
    for (int i = 0; i < 3; i++) *reinterpret_cast<uint4*>(yp + 512 + i * Y_BOX_BYTES) = y[i];
}

__device__ __forceinline__ float gelu2(float u) {
    float t = fmaf(u, u, GELU_C0K);
    float a = t * u;
    float th = tanh_approx(a);
    return fmaf(u, th, u);
}

__device__ __forceinline__ void tma_x_tile(uint32_t dst, const CUtensorMap* tmx, uint32_t bar, int tile) {
    mbar_expect_tx(bar, Y_TILE_BYTES);
#pragma unroll
    for (int i = 0; i < 3; i++) tma_load_2d(dst + i * Y_BOX_BYTES, tmx, bar, i * 32, tile * TILE_M);
}

__global__ void __launch_bounds__(NTHR, 1)
k_stats(const __grid_constant__ CUtensorMap tm_x, const __grid_constant__ CUtensorMap tm_w1,
        const __nv_bfloat16* __restrict__ dw, const __nv_bfloat16* __restrict__ w2,
        const __nv_bfloat16* __restrict__ grn_g, const __nv_bfloat16* __restrict__ grn_b) {
    extern __shared__ __align__(1024) unsigned char smem[];
    unsigned char* s_w1 = smem;
    unsigned char* s_y = smem + 73728;
    float* s_dw = reinterpret_cast<float*>(smem + 73728 + NWG * 2 * Y_TILE_BYTES);
    float* s_red = s_dw + 128;
    uint64_t* s_bar = reinterpret_cast<uint64_t*>(s_red + C_H);

    const int tid = threadIdx.x;
    const int wg = tid >> 7;
    const int warp = (tid >> 5) & 3;
    const int lane = tid & 31;
    const int q = lane & 3;
    const int nwg = gridDim.x * NWG;
    int tile = blockIdx.x * NWG + wg;

    TS0(0);
    if (tid == 0) {
        for (int i = 0; i < 1 + 2 * NWG; i++) mbar_init(smem_u32(s_bar + i), 1);
        asm volatile("fence.mbarrier_init.release.cluster;\n" ::: "memory");
    }
    __shared__ float s_gb[2 * C_H];
    if (tid < C_IN) s_dw[tid] = __bfloat162float(dw[tid]);
    if (tid < C_H) { s_gb[tid] = __bfloat162float(grn_g[tid]); s_gb[C_H + tid] = __bfloat162float(grn_b[tid]); }
    for (int i = tid; i < C_H; i += NTHR) s_red[i] = 0.f;
    __syncthreads();
    const uint32_t ybuf0 = smem_u32(s_y + wg * 2 * Y_TILE_BYTES);
    const uint32_t bar_y = smem_u32(s_bar + 1 + 2 * wg);
    if (tid == 0) {
        mbar_expect_tx(smem_u32(s_bar), 6 * W1_BOX_BYTES);
        for (int i = 0; i < 6; i++) tma_load_2d(smem_u32(s_w1) + i * W1_BOX_BYTES, &tm_w1, smem_u32(s_bar), i * 64, 0);
    }
    if ((tid & 127) == 0 && tile < NTILES) tma_x_tile(ybuf0, &tm_x, bar_y, tile);

    asm volatile("griddepcontrol.launch_dependents;\n" ::: "memory");
    if (blockIdx.x == 0) {
        prefetch_l2(reinterpret_cast<const unsigned char*>(w2) + tid * 128);
        if (tid < 64) prefetch_l2(reinterpret_cast<const unsigned char*>(w2) + (512 + tid) * 128);
    }
    float ss[12];
#pragma unroll
    for (int i = 0; i < 12; i++) ss[i] = 0.f;

    const uint64_t w1_desc = make_desc(smem_u32(s_w1), W1_BOX_BYTES, 1024, 1);
    const int rl = warp * 16 + (lane >> 2);
    const int yoff = rl * 64 + ((q ^ ((rl >> 1) & 3)) * 16);
    mbar_wait(smem_u32(s_bar), 0);

    int it = 0;
    for (; tile < NTILES; tile += nwg, it++) {
        const int buf = it & 1;
        if ((tid & 127) == 0 && tile + nwg < NTILES) tma_x_tile(ybuf0 + (buf ^ 1) * Y_TILE_BYTES, &tm_x, bar_y + (buf ^ 1) * 8, tile + nwg);
        mbar_wait(bar_y + buf * 8, (it >> 1) & 1);
        unsigned char* ytile = s_y + (wg * 2 + buf) * Y_TILE_BYTES;
        ln_tile_inplace(ytile + yoff, s_dw + 8 * q);
        proxy_fence();
        wg_bar(1 + wg);
        const uint64_t y_desc = make_desc(smem_u32(ytile), 16, 512, 2);
        float S[2][32];
        wg_fence();
#pragma unroll
        for (int t = 0; t < 6; t++)
            wgmma_ss_n64_tA(S[0], w1_desc + ((t * 2048) >> 4), y_desc + (((t >> 1) * Y_BOX_BYTES + (t & 1) * 32) >> 4), t != 0);
        wg_commit();
#pragma unroll
        for (int m = 0; m < 6; m++) {
            if (m + 1 < 6) {
                wg_fence();
#pragma unroll
                for (int t = 0; t < 6; t++)
                    wgmma_ss_n64_tA(S[(m + 1) & 1], w1_desc + (((m + 1) * W1_BOX_BYTES + t * 2048) >> 4),
                                    y_desc + (((t >> 1) * Y_BOX_BYTES + (t & 1) * 32) >> 4), t != 0);
                wg_commit();
                wg_wait<1>();
            } else {
                wg_wait<0>();
            }
            float(&Sc)[32] = S[m & 1];
            float a0 = ss[2 * m], a1 = ss[2 * m + 1];
#pragma unroll
            for (int j = 0; j < 8; j++) {
                float g0 = gelu2(Sc[4 * j]);
                float g1 = gelu2(Sc[4 * j + 1]);
                float g2 = gelu2(Sc[4 * j + 2]);
                float g3 = gelu2(Sc[4 * j + 3]);
                a0 = fmaf(g0, g0, a0);
                a1 = fmaf(g2, g2, a1);
                a0 = fmaf(g1, g1, a0);
                a1 = fmaf(g3, g3, a1);
            }
            ss[2 * m] = a0;
            ss[2 * m + 1] = a1;
        }
        wg_bar(1 + wg);
    }
    TS0(1);
#pragma unroll
    for (int i = 0; i < 12; i++) {
        float v = ss[i];
        v += __shfl_xor_sync(0xffffffffu, v, 1);
        v += __shfl_xor_sync(0xffffffffu, v, 2);
        if (q == 0) {
            int m = i >> 1, hh = i & 1;
            atomicAdd(&s_red[m * 64 + warp * 16 + hh * 8 + (lane >> 2)], v);
        }
    }
    __syncthreads();
    const float sc = 0.25f / (GELU_KAPPA * GELU_KAPPA);
    for (int i = tid; i < C_H; i += NTHR) atomicAdd(&g_sum[i], s_red[i] * sc);
    __threadfence();
    __syncthreads();
    __shared__ unsigned int s_last;
    if (tid == 0) s_last = (atomicAdd(&g_done, 1u) == gridDim.x - 1);
    __syncthreads();
    if (!s_last) return;
    TS(2);
    __threadfence();
    float* s_s = s_red;
    float* s_tmp = s_dw;
    float lsum = 0.f;
    if (tid < C_H) {
        float gx = sqrtf(__ldcg(&g_sum[tid]) + 1e-6f);
        g_sum[tid] = 0.f;
        s_s[tid] = gx;
        lsum = gx;
    }
    uint4 w2v[384 * 12 / NTHR];
#pragma unroll
    for (int i = 0; i < 384 * 12 / NTHR; i++) {
        int it2 = tid + i * NTHR;
        int kr = it2 & 7;
        int nb = (it2 >> 3) % 12;
        int kb = (it2 >> 3) / 12;
        w2v[i] = __ldg(reinterpret_cast<const uint4*>(w2 + (kb * 8 + kr) * C_IN + nb * 8));
    }
#pragma unroll
    for (int o = 16; o > 0; o >>= 1) lsum += __shfl_xor_sync(0xffffffffu, lsum, o);
    if (lane == 0) s_tmp[tid >> 5] = lsum;
    if (tid == 0) g_done = 0;
    __syncthreads();
    float tot = 0.f;
#pragma unroll
    for (int i = 0; i < NTHR / 32; i++) tot += s_tmp[i];
    float inv = 1.0f / (tot * (1.0f / C_H) + 1e-6f);
    __syncthreads();
    if (tid < C_H) s_s[tid] = (0.5f / GELU_KAPPA) * (1.0f + s_gb[tid] * (s_s[tid] * inv));
    if (tid < C_IN) s_tmp[tid] = 0.f;
    __syncthreads();
    TS(3);
    {
        float a0 = 0.f, a1 = 0.f, a2 = 0.f;
        int kbase = (tid >> 5) * (C_H / (NTHR / 32));
#pragma unroll
        for (int k = kbase; k < kbase + C_H / (NTHR / 32); k++) {
            float b = s_gb[C_H + k];
            a0 = fmaf(b, __bfloat162float(w2[k * C_IN + lane]), a0);
            a1 = fmaf(b, __bfloat162float(w2[k * C_IN + lane + 32]), a1);
            a2 = fmaf(b, __bfloat162float(w2[k * C_IN + lane + 64]), a2);
        }
        atomicAdd(&s_tmp[lane], a0);
        atomicAdd(&s_tmp[lane + 32], a1);
        atomicAdd(&s_tmp[lane + 64], a2);
    }
#pragma unroll
    for (int i = 0; i < 384 * 12 / NTHR; i++) {
        int it2 = tid + i * NTHR;
        int kr = it2 & 7;
        int nb = (it2 >> 3) % 12;
        int kb = (it2 >> 3) / 12;
        float sk = s_s[kb * 8 + kr];
        uint4 v = w2v[i];
        uint4 o;
        o.x = pack_bf16(sk * bf_lo(v.x), sk * bf_hi(v.x));
        o.y = pack_bf16(sk * bf_lo(v.y), sk * bf_hi(v.y));
        o.z = pack_bf16(sk * bf_lo(v.z), sk * bf_hi(v.z));
        o.w = pack_bf16(sk * bf_lo(v.w), sk * bf_hi(v.w));
        *reinterpret_cast<uint4*>(g_w2img + nb * W2_SBO + kb * W2_LBO + kr * 16) = o;
    }
    __syncthreads();
    if (tid < C_IN) g_c[tid] = s_tmp[tid];
    TS(4);
}

#define NWG2 3
#define NTHR2 (NWG2 * 128)

__device__ __forceinline__ void wgmma_rs_n64(float (&d)[32], uint32_t a0, uint32_t a1, uint32_t a2, uint32_t a3,
                                             uint64_t bdesc, int scale_d) {
    asm volatile(
        "{\n.reg .pred p;\nsetp.ne.b32 p, %37, 0;\n"
        "wgmma.mma_async.sync.aligned.m64n64k16.f32.bf16.bf16 " ACC32_STR ", {%32, %33, %34, %35}, %36, p, 1, 1, 1;\n}\n"
        : ACC32(d)
        : "r"(a0), "r"(a1), "r"(a2), "r"(a3), "l"(bdesc), "r"(scale_d));
}
__device__ __forceinline__ void ldsm_x4(uint32_t addr, uint32_t& r0, uint32_t& r1, uint32_t& r2, uint32_t& r3) {
    asm volatile("ldmatrix.sync.aligned.m8n8.x4.shared.b16 {%0, %1, %2, %3}, [%4];\n"
                 : "=r"(r0), "=r"(r1), "=r"(r2), "=r"(r3) : "r"(addr) : "memory");
}
__device__ __forceinline__ void stsm_x4(uint32_t addr, uint32_t r0, uint32_t r1, uint32_t r2, uint32_t r3) {
    asm volatile("stmatrix.sync.aligned.m8n8.x4.shared.b16 [%0], {%1, %2, %3, %4};\n" ::"r"(addr), "r"(r0), "r"(r1), "r"(r2),
                 "r"(r3) : "memory");
}
__device__ __forceinline__ void tma_store_2d(const CUtensorMap* tm, uint32_t src, int c0, int c1) {
    asm volatile("cp.async.bulk.tensor.2d.global.shared::cta.bulk_group [%0, {%2, %3}], [%1];\n" ::"l"(
                     reinterpret_cast<uint64_t>(tm)), "r"(src), "r"(c0), "r"(c1) : "memory");
}

__device__ __forceinline__ void ln_frag(uint32_t (&f)[6][4], const float* __restrict__ s_dwq) {
    float xa[24], xb[24], dwf[24];
    float sa = 0.f, sb = 0.f;
#pragma unroll
    for (int t = 0; t < 6; t++) {
#pragma unroll
        for (int h = 0; h < 2; h++) {
            float2 d = *reinterpret_cast<const float2*>(s_dwq + 16 * t + 8 * h);
            int i = t * 4 + h * 2;
            dwf[i] = d.x; dwf[i + 1] = d.y;
            xa[i] = bf_lo(f[t][2 * h]); xa[i + 1] = bf_hi(f[t][2 * h]);
            xb[i] = bf_lo(f[t][2 * h + 1]); xb[i + 1] = bf_hi(f[t][2 * h + 1]);
            sa = fmaf(xa[i], d.x, sa); sa = fmaf(xa[i + 1], d.y, sa);
            sb = fmaf(xb[i], d.x, sb); sb = fmaf(xb[i + 1], d.y, sb);
        }
    }
    sa += __shfl_xor_sync(0xffffffffu, sa, 1);
    sb += __shfl_xor_sync(0xffffffffu, sb, 1);
    sa += __shfl_xor_sync(0xffffffffu, sa, 2);
    sb += __shfl_xor_sync(0xffffffffu, sb, 2);
    float ma = sa * (-1.0f / C_IN), mb = sb * (-1.0f / C_IN);
    float va = 0.f, vb = 0.f;
#pragma unroll
    for (int i = 0; i < 24; i++) {
        xa[i] = fmaf(xa[i], dwf[i], ma);
        xb[i] = fmaf(xb[i], dwf[i], mb);
        va = fmaf(xa[i], xa[i], va);
        vb = fmaf(xb[i], xb[i], vb);
    }
    va += __shfl_xor_sync(0xffffffffu, va, 1);
    vb += __shfl_xor_sync(0xffffffffu, vb, 1);
    va += __shfl_xor_sync(0xffffffffu, va, 2);
    vb += __shfl_xor_sync(0xffffffffu, vb, 2);
    float ra = rsqrtf(va * (1.0f / C_IN) + 1e-5f) * GELU_KAPPA;
    float rb = rsqrtf(vb * (1.0f / C_IN) + 1e-5f) * GELU_KAPPA;
#pragma unroll
    for (int t = 0; t < 6; t++) {
#pragma unroll
        for (int h = 0; h < 2; h++) {
            int i = t * 4 + h * 2;
            f[t][2 * h] = pack_bf16(xa[i] * ra, xa[i + 1] * ra);
            f[t][2 * h + 1] = pack_bf16(xb[i] * rb, xb[i + 1] * rb);
        }
    }
}

__global__ void __launch_bounds__(NTHR2, 1)
k_main(const __grid_constant__ CUtensorMap tm_x, const __grid_constant__ CUtensorMap tm_w1,
       const __grid_constant__ CUtensorMap tm_out, const __nv_bfloat16* __restrict__ dw) {
    extern __shared__ __align__(1024) unsigned char smem[];
    unsigned char* s_w1 = smem;
    unsigned char* s_w2 = smem + 73728;
    unsigned char* s_x = smem + 2 * 73728;
    float* s_dw = reinterpret_cast<float*>(smem + 2 * 73728 + NWG2 * 2 * Y_TILE_BYTES);
    float* s_c = s_dw + 128;
    uint64_t* s_bar = reinterpret_cast<uint64_t*>(s_c + 128);

    const int tid = threadIdx.x;
    const int wg = tid >> 7;
    const int warp = (tid >> 5) & 3;
    const int lane = tid & 31;
    const int q = lane & 3;
    const int nwg = gridDim.x * NWG2;
    int tile = blockIdx.x * NWG2 + wg;

    TS0(5);
    const uint32_t xbuf0 = smem_u32(s_x + wg * 2 * Y_TILE_BYTES);
    const uint32_t bar_x = smem_u32(s_bar + 1 + 2 * wg);
    if (tid == 0) {
        for (int i = 0; i < 1 + 2 * NWG2; i++) mbar_init(smem_u32(s_bar + i), 1);
        asm volatile("fence.mbarrier_init.release.cluster;\n" ::: "memory");
    }
    if (tid < C_IN) s_dw[tid] = __bfloat162float(dw[tid]);
    __syncthreads();
    if ((tid & 127) == 0 && tile < NTILES) tma_x_tile(xbuf0, &tm_x, bar_x, tile);
    if (tid == 0) {
        mbar_expect_tx(smem_u32(s_bar), 6 * W1_BOX_BYTES + 73728);
        for (int i = 0; i < 6; i++) tma_load_2d(smem_u32(s_w1) + i * W1_BOX_BYTES, &tm_w1, smem_u32(s_bar), i * 64, 0);
    }
    asm volatile("griddepcontrol.wait;\n" ::: "memory");
    if (tid < C_IN) s_c[tid] = __ldcg(&g_c[tid]);
    if (tid == 0) {
        for (int i = 0; i < 6; i++)
            asm volatile("cp.async.bulk.shared::cluster.global.mbarrier::complete_tx::bytes [%0], [%1], %2, [%3];\n" ::"r"(
                             smem_u32(s_w2) + i * 12288),
                         "l"(g_w2img + i * 12288), "r"(12288), "r"(smem_u32(s_bar))
                         : "memory");
    }
    __syncthreads();
    mbar_wait(smem_u32(s_bar), 0);
    TS0(6);

    const uint64_t w1_desc = make_desc(smem_u32(s_w1), W1_BOX_BYTES, 1024, 1);
    const uint64_t w2_desc = make_desc(smem_u32(s_w2), W2_LBO, W2_SBO, 0);
    const int lrow = warp * 16 + ((lane >> 3) & 1) * 8 + (lane & 7);
    const int lhalf = lane >> 4;
    const int lsw = (lrow >> 1) & 3;
    const uint32_t loff0 = lrow * 64 + (((0 + lhalf) ^ lsw) << 4);
    const uint32_t loff1 = lrow * 64 + (((2 + lhalf) ^ lsw) << 4);

    int it = 0;
    for (; tile < NTILES; tile += nwg, it++) {
        const int buf = it & 1;
        const uint32_t xb = xbuf0 + buf * Y_TILE_BYTES;
        if ((tid & 127) == 0 && tile + nwg < NTILES) {
            asm volatile("cp.async.bulk.wait_group.read 0;\n" ::: "memory");
            tma_x_tile(xbuf0 + (buf ^ 1) * Y_TILE_BYTES, &tm_x, bar_x + (buf ^ 1) * 8, tile + nwg);
        }
        mbar_wait(bar_x + buf * 8, (it >> 1) & 1);
        uint32_t f[6][4];
#pragma unroll
        for (int t = 0; t < 6; t++)
            ldsm_x4(xb + (t >> 1) * Y_BOX_BYTES + ((t & 1) ? loff1 : loff0), f[t][0], f[t][1], f[t][2], f[t][3]);
        ln_frag(f, s_dw + 2 * q);

        float O[48];
#pragma unroll
        for (int j = 0; j < 12; j++) {
            float2 cc = *reinterpret_cast<const float2*>(&s_c[8 * j + 2 * q]);
            O[4 * j] = cc.x; O[4 * j + 1] = cc.y; O[4 * j + 2] = cc.x; O[4 * j + 3] = cc.y;
        }
        float S[32];
        uint32_t hf[16];
        wg_fence();
#pragma unroll
        for (int t = 0; t < 6; t++) wgmma_rs_n64(S, f[t][0], f[t][1], f[t][2], f[t][3], w1_desc + ((t * 2048) >> 4), t != 0);
        wg_commit();
#pragma unroll
        for (int c = 0; c < 6; c++) {
            wg_wait<0>();
#pragma unroll
            for (int j = 0; j < 8; j++) {
                float g0 = gelu2(S[4 * j]);
                float g1 = gelu2(S[4 * j + 1]);
                float g2 = gelu2(S[4 * j + 2]);
                float g3 = gelu2(S[4 * j + 3]);
                hf[2 * j] = pack_bf16(g0, g1);
                hf[2 * j + 1] = pack_bf16(g2, g3);
            }
            wg_fence();
#pragma unroll
            for (int t = 0; t < 4; t++)
                wgmma_n96(O, hf[4 * t], hf[4 * t + 1], hf[4 * t + 2], hf[4 * t + 3],
                          w2_desc + (((c * 8 + 2 * t) * W2_LBO) >> 4));
            if (c + 1 < 6) {
#pragma unroll
                for (int t = 0; t < 6; t++)
                    wgmma_rs_n64(S, f[t][0], f[t][1], f[t][2], f[t][3],
                                 w1_desc + (((c + 1) * W1_BOX_BYTES + t * 2048) >> 4), t != 0);
            }
            wg_commit();
        }
        uint32_t xr[6][4];
#pragma unroll
        for (int t = 0; t < 6; t++)
            ldsm_x4(xb + (t >> 1) * Y_BOX_BYTES + ((t & 1) ? loff1 : loff0), xr[t][0], xr[t][1], xr[t][2], xr[t][3]);
        wg_wait<0>();
#pragma unroll
        for (int t = 0; t < 6; t++) {
            uint32_t o0 = pack_bf16(bf_lo(xr[t][0]) + O[8 * t + 0], bf_hi(xr[t][0]) + O[8 * t + 1]);
            uint32_t o1 = pack_bf16(bf_lo(xr[t][1]) + O[8 * t + 2], bf_hi(xr[t][1]) + O[8 * t + 3]);
            uint32_t o2 = pack_bf16(bf_lo(xr[t][2]) + O[8 * t + 4], bf_hi(xr[t][2]) + O[8 * t + 5]);
            uint32_t o3 = pack_bf16(bf_lo(xr[t][3]) + O[8 * t + 6], bf_hi(xr[t][3]) + O[8 * t + 7]);
            stsm_x4(xb + (t >> 1) * Y_BOX_BYTES + ((t & 1) ? loff1 : loff0), o0, o1, o2, o3);
        }
        proxy_fence();
        wg_bar(1 + wg);
        if ((tid & 127) == 0) {
#pragma unroll
            for (int i = 0; i < 3; i++) tma_store_2d(&tm_out, xb + i * Y_BOX_BYTES, i * 32, tile * TILE_M);
            asm volatile("cp.async.bulk.commit_group;\n" ::: "memory");
        }
    }
    if ((tid & 127) == 0) asm volatile("cp.async.bulk.wait_group 0;\n" ::: "memory");
    TS0(7);
}

#define SMEM1 (73728 + NWG * 2 * Y_TILE_BYTES + 512 + 1536 + 128)
#define SMEM2 (2 * 73728 + NWG2 * 2 * Y_TILE_BYTES + 512 + 512 + 64)

typedef CUresult (*PFN_encodeTiled)(CUtensorMap*, CUtensorMapDataType, cuuint32_t, void*, const cuuint64_t*, const cuuint64_t*,
                                    const cuuint32_t*, const cuuint32_t*, CUtensorMapInterleave, CUtensorMapSwizzle,
                                    CUtensorMapL2promotion, CUtensorMapFloatOOBfill);

extern "C" void kernel_launch(void* const* d_in, const int* in_sizes, int n_in, void* d_out, int out_size) {
    const __nv_bfloat16* x = (const __nv_bfloat16*)d_in[0];
    const __nv_bfloat16* dw = (const __nv_bfloat16*)d_in[1];
    const __nv_bfloat16* w1 = (const __nv_bfloat16*)d_in[2];
    const __nv_bfloat16* w2 = (const __nv_bfloat16*)d_in[3];
    const __nv_bfloat16* grn_g = (const __nv_bfloat16*)d_in[4];
    const __nv_bfloat16* grn_b = (const __nv_bfloat16*)d_in[5];

    static int n_sm = 0;
    static CUtensorMap tm_x, tm_w1, tm_out;
    static const void* last_x = nullptr;
    static const void* last_w1 = nullptr;
    static const void* last_out = nullptr;
    static PFN_encodeTiled encode = nullptr;
    if (n_sm == 0) {
        int dev = 0;
        cudaGetDevice(&dev);
        cudaDeviceGetAttribute(&n_sm, cudaDevAttrMultiProcessorCount, dev);
        if (n_sm > MAX_CTAS) n_sm = MAX_CTAS;
        cudaFuncSetAttribute(k_stats, cudaFuncAttributeMaxDynamicSharedMemorySize, SMEM1);
        cudaFuncSetAttribute(k_main, cudaFuncAttributeMaxDynamicSharedMemorySize, SMEM2);
        cudaDriverEntryPointQueryResult qres;
        void* fn = nullptr;
        cudaGetDriverEntryPoint("cuTensorMapEncodeTiled", &fn, cudaEnableDefault, &qres);
        encode = (PFN_encodeTiled)fn;
    }
    if (last_x != x || last_w1 != w1 || last_out != d_out) {
        cuuint64_t dims[2] = {96, (cuuint64_t)NROWS};
        cuuint64_t strides[1] = {192};
        cuuint32_t box[2] = {32, 64};
        cuuint32_t es[2] = {1, 1};
        encode(&tm_x, CU_TENSOR_MAP_DATA_TYPE_BFLOAT16, 2, (void*)x, dims, strides, box, es, CU_TENSOR_MAP_INTERLEAVE_NONE,
               CU_TENSOR_MAP_SWIZZLE_64B, CU_TENSOR_MAP_L2_PROMOTION_L2_128B, CU_TENSOR_MAP_FLOAT_OOB_FILL_NONE);
        encode(&tm_out, CU_TENSOR_MAP_DATA_TYPE_BFLOAT16, 2, d_out, dims, strides, box, es, CU_TENSOR_MAP_INTERLEAVE_NONE,
               CU_TENSOR_MAP_SWIZZLE_64B, CU_TENSOR_MAP_L2_PROMOTION_L2_128B, CU_TENSOR_MAP_FLOAT_OOB_FILL_NONE);
        cuuint64_t dimsw[2] = {384, 96};
        cuuint64_t stridesw[1] = {768};
        cuuint32_t boxw[2] = {64, 96};
        encode(&tm_w1, CU_TENSOR_MAP_DATA_TYPE_BFLOAT16, 2, (void*)w1, dimsw, stridesw, boxw, es, CU_TENSOR_MAP_INTERLEAVE_NONE,
               CU_TENSOR_MAP_SWIZZLE_128B, CU_TENSOR_MAP_L2_PROMOTION_L2_128B, CU_TENSOR_MAP_FLOAT_OOB_FILL_NONE);
        last_x = x;
        last_w1 = w1;
        last_out = d_out;
    }
    k_stats<<<n_sm, NTHR, SMEM1>>>(tm_x, tm_w1, dw, w2, grn_g, grn_b);
    cudaLaunchConfig_t cfg = {};
    cfg.gridDim = dim3(n_sm);
    cfg.blockDim = dim3(NTHR2);
    cfg.dynamicSmemBytes = SMEM2;
    cfg.stream = cudaStreamPerThread;
    cudaLaunchAttribute attr[1];
    attr[0].id = cudaLaunchAttributeProgrammaticStreamSerialization;
    attr[0].val.programmaticStreamSerializationAllowed = 1;
    cfg.attrs = attr;
    cfg.numAttrs = 1;
    cudaLaunchKernelEx(&cfg, k_main, tm_x, tm_w1, tm_out, dw);
}
```
